```python
import torch

def _softmax(x, axis=-1):
    return torch.softmax(x, dim=axis)
def _gelu(x):
    return torch.nn.functional.gelu(x, approximate="tanh")
def _silu(x):
    return torch.nn.functional.silu(x)
def _sigmoid(x):
    return torch.sigmoid(x)
def _layernorm(x, axis=-1, eps=1e-5):
    m = x.mean(dim=axis, keepdim=True)
    v = x.var(dim=axis, keepdim=True, unbiased=False)
    return (x - m) / torch.sqrt(v + eps)
def _scatter_add(tgt, idx, src, axis=0):
    return tgt.clone().index_add_(axis, idx, src)
def _segment_sum(src, seg, n):
    out = torch.zeros((n,) + src.shape[1:], dtype=src.dtype)
    return out.index_add_(0, seg, src)
def _pad(x, pw):
    flat = tuple(v for pair in reversed(pw) for v in pair)
    return torch.nn.functional.pad(x, flat)

kernel_name = 'sequential_preLN__grouped_kv_mqa__dense_activation_silu__prompt'

def setup_inputs():

    _w = (lambda a: (lambda t: t.to(torch.bfloat16) if t.is_floating_point() else t)(torch.as_tensor(a)))
    def _A_setup():
        B, S, D, H = 1, 2048, 512, 32
        Dh = D // H
        return {
            "x": _w((lambda *s: torch.randn(*s, dtype=torch.bfloat16) * 0.05)(B, S, D)),
            "wq": _w((lambda *s: torch.randn(*s, dtype=torch.bfloat16) * 0.05)(D, H * Dh)),
            "wk": _w((lambda *s: torch.randn(*s, dtype=torch.bfloat16) * 0.05)(D, Dh)),
            "wv": _w((lambda *s: torch.randn(*s, dtype=torch.bfloat16) * 0.05)(D, Dh)),
            "wo": _w((lambda *s: torch.randn(*s, dtype=torch.bfloat16) * 0.05)(H * Dh, D)),
        }
    _A_in = _A_setup()

    def _B_setup():
        B, S, D, F = 1, 2048, 512, 1376
        return {
            "x": _w((lambda *s: torch.randn(*s, dtype=torch.bfloat16) * 0.05)(B, S, D)),
            "w1": _w((lambda *s: torch.randn(*s, dtype=torch.bfloat16) * 0.8)(D, F) * (D ** -0.5)),
            "w2": _w((lambda *s: torch.randn(*s, dtype=torch.bfloat16) * 0.2)(F, D) * (F ** -0.5)),
        }
    _B_in = _B_setup()

    return {
        "A_x": _A_in["x"],
        "A_wq": _A_in["wq"],
        "A_wk": _A_in["wk"],
        "A_wv": _A_in["wv"],
        "A_wo": _A_in["wo"],
        "B_x": _B_in["x"],
        "B_w1": _B_in["w1"],
        "B_w2": _B_in["w2"],
    }

def reference(A_x, A_wq, A_wk, A_wv, A_wo, B_x, B_w1, B_w2):
    def _A_ref(x, wq, wk, wv, wo):
        B, S, D = x.shape
        H = 32
        Dh = D // H
        q = (lambda x, *d: x.permute(*d))((x @ wq).reshape(B, S, H, Dh), 0, 2, 1, 3)
        k = x @ wk
        v = x @ wv
        scores = torch.einsum("bhqd,bkd->bhqk", q, k) * (Dh ** -0.5)
        p = _softmax(scores, axis=-1)
        o = torch.einsum("bhqk,bkd->bhqd", p, v)
        return (lambda x, *d: x.permute(*d))(o, 0, 2, 1, 3).reshape(B, S, H * Dh) @ wo

    def _B_ref(x, w1, w2):
        h = torch.einsum("bsd,df->bsf", x, w1)
        h = _silu(h)
        out = torch.einsum("bsf,fd->bsd", h, w2)
        return out

    x = A_x
    h = x + _A_ref(_layernorm(x, axis=-1), A_wq, A_wk, A_wv, A_wo)
    h2 = h + _B_ref(_layernorm(h, axis=-1), B_w1, B_w2)
    return h2
```

```cpp
#include <cuda_runtime.h>
#include <cuda_bf16.h>
#include <cuda_fp16.h>
#include <cuda.h>
#include <stdint.h>

namespace {

constexpr int S_ = 2048, D_ = 512, F_ = 1376;
constexpr int NMAIN = 128, NAUX = 4, NCTA = NMAIN + NAUX;
constexpr float LN_EPS = 1e-5f;
constexpr float QK_SCALE_LOG2 = 0.25f * 1.4426950408889634f;

__device__ __align__(1024) uint8_t g_kv[8 * 16384];
__device__ __align__(1024) uint8_t g_kp[8 * 8192];
__device__ __align__(16) float2 g_st1[S_];
__device__ __align__(16) float2 g_kmax[NMAIN];
__device__ __align__(1024) uint8_t g_o[32 * 65536];
__device__ __align__(1024) uint8_t g_h[32 * 65536];
__device__ __align__(16) float2 g_st2[32 * 8 * 64];
__device__ __align__(1024) uint8_t g_hh[32 * 172 * 1024 + 8192];
__device__ __align__(16) float g_cs1[F_ + 32];
constexpr int CNT_STRIDE = 32;
enum { C_KV = 0, C_AUX = 1, C_DONE = 2, C_O = 4, C_H = C_O + 32, C_HH = C_H + 32, C_NUM = C_HH + 64 };
__device__ unsigned int g_cnt[C_NUM * CNT_STRIDE];
#define TSTAMP(i) do {} while (0)

constexpr int KB = 1024;
constexpr int CHB = 20 * KB;
constexpr int OFF_Q = 160 * KB;
constexpr int OFF_STG = 0;
constexpr int OFF_X = 32 * KB;
constexpr int OFF_WQ = 160 * KB;
constexpr int OFF_RING = 176 * KB;
constexpr int OFF_MISC = 224 * KB;
constexpr int OFF_BAR = OFF_MISC;
constexpr int OFF_CS = OFF_MISC + 512;
constexpr int OFF_SC = OFF_CS + 768;
constexpr int SMEM_BYTES = OFF_MISC + 2048;
enum { B_XQ = 0, B_KV0 = 8, B_KV1 = 9, B_WOA = 10, B_WOB = 11, B_OF = 12  , B_ADONE = 20, B_PDONE = 21  ,
       B_W1F = 23  , B_W1E = 31  , B_W2F = 39  , B_RF = 50  , B_RE = 56  , B_RED = 62  , B_NUM = 64 };
enum { SC_EPOCH = 0, SC_QMAX = 1, SC_KMAX = 2, SC_VMAX = 3, SC_FREE = 4   };

__device__ __forceinline__ uint32_t s2u(const void* p) { return (uint32_t)__cvta_generic_to_shared(p); }
__device__ __forceinline__ void mbar_init(uint32_t b, int c) { asm volatile("mbarrier.init.shared::cta.b64 [%0], %1;" ::"r"(b), "r"(c) : "memory"); }
__device__ __forceinline__ void mbar_expect(uint32_t b, uint32_t n) { asm volatile("mbarrier.arrive.expect_tx.shared::cta.b64 _, [%0], %1;" ::"r"(b), "r"(n) : "memory"); }
__device__ __forceinline__ void mbar_arrive(uint32_t b) { asm volatile("mbarrier.arrive.shared::cta.b64 _, [%0];" ::"r"(b) : "memory"); }
__device__ __forceinline__ void mbar_wait(uint32_t b, uint32_t ph) {
  asm volatile("{\n.reg .pred p;\n.reg .u32 n;\nmov.u32 n, 0;\n"
               "W%=:\nmbarrier.try_wait.parity.shared::cta.b64 p, [%0], %1;\n@p bra D%=;\n"
               "add.u32 n, n, 1;\nsetp.lt.u32 p, n, 4000000;\n@p bra W%=;\ntrap;\nD%=:\n}" ::"r"(b), "r"(ph) : "memory");
}
__device__ __forceinline__ void mbar_wait_cluster(uint32_t b, uint32_t ph) {
  asm volatile("{\n.reg .pred p;\n.reg .u32 n;\nmov.u32 n, 0;\n"
               "W%=:\nmbarrier.try_wait.parity.acquire.cluster.shared::cta.b64 p, [%0], %1;\n@p bra D%=;\n"
               "add.u32 n, n, 1;\nsetp.lt.u32 p, n, 4000000;\n@p bra W%=;\ntrap;\nD%=:\n}" ::"r"(b), "r"(ph) : "memory");
}
__device__ __forceinline__ void bulk_g2s(uint32_t dst, const void* src, uint32_t n, uint32_t bar) {
  asm volatile("cp.async.bulk.shared::cluster.global.mbarrier::complete_tx::bytes [%0], [%1], %2, [%3];" ::"r"(dst), "l"(src), "r"(n), "r"(bar) : "memory");
}
__device__ __forceinline__ void tma2d(uint32_t dst, const CUtensorMap* m, int c0, int c1, uint32_t bar) {
  asm volatile("cp.async.bulk.tensor.2d.shared::cluster.global.mbarrier::complete_tx::bytes [%0], [%1, {%3, %4}], [%2];"
               ::"r"(dst), "l"(m), "r"(bar), "r"(c0), "r"(c1) : "memory");
}
__device__ __forceinline__ void l2_prefetch(const void* p, uint32_t n) { asm volatile("cp.async.bulk.prefetch.L2.global [%0], %1;" ::"l"(p), "r"(n) : "memory"); }
__device__ __forceinline__ void fence_async_smem() { asm volatile("fence.proxy.async.shared::cta;" ::: "memory"); }
__device__ __forceinline__ void fence_async_all() { asm volatile("fence.proxy.async;" ::: "memory"); }
__device__ __forceinline__ void bar_sync(int id, int n) { asm volatile("bar.sync %0, %1;" ::"r"(id), "r"(n) : "memory"); }
__device__ __forceinline__ void flag_add(int c) { asm volatile("red.release.gpu.global.add.u32 [%0], 1;" ::"l"(&g_cnt[c * CNT_STRIDE]) : "memory"); }
__device__ __forceinline__ void flag_wait(int c, unsigned int target) {
  unsigned int v; int n = 0;
  do { asm volatile("ld.acquire.gpu.global.u32 %0, [%1];" : "=r"(v) : "l"(&g_cnt[c * CNT_STRIDE]) : "memory");
       if (++n > 20000000) __trap(); } while ((int)(v - target) < 0);
  fence_async_all();
}
__device__ __forceinline__ void wg_fence() { asm volatile("wgmma.fence.sync.aligned;" ::: "memory"); }
__device__ __forceinline__ void wg_commit() { asm volatile("wgmma.commit_group.sync.aligned;" ::: "memory"); }
template <int N> __device__ __forceinline__ void wg_wait() { asm volatile("wgmma.wait_group.sync.aligned %0;" ::"n"(N) : "memory"); }
__device__ __forceinline__ uint64_t mkdesc(uint32_t addr, uint32_t lbo, uint32_t sbo, uint32_t swz = 0) {
  return (uint64_t)((addr & 0x3FFFF) >> 4) | ((uint64_t)(lbo >> 4) << 16) | ((uint64_t)(sbo >> 4) << 32) | ((uint64_t)swz << 62);
}
template <int N> __device__ __forceinline__ void pin(float (&d)[N]) {
#pragma unroll
  for (int i = 0; i < N; i++) asm volatile("" : "+f"(d[i])::"memory");
}
template <int N> __device__ __forceinline__ void pin(uint32_t (&d)[N]) {
#pragma unroll
  for (int i = 0; i < N; i++) asm volatile("" : "+r"(d[i])::"memory");
}
__device__ __forceinline__ uint32_t pack_bf16(float lo, float hi) { uint32_t r; asm("cvt.rn.bf16x2.f32 %0, %1, %2;" : "=r"(r) : "f"(hi), "f"(lo)); return r; }
__device__ __forceinline__ uint32_t pack_f16(float lo, float hi) { uint32_t r; asm("cvt.rn.f16x2.f32 %0, %1, %2;" : "=r"(r) : "f"(hi), "f"(lo)); return r; }
__device__ __forceinline__ float bf_lo(uint32_t u) { return __uint_as_float(u << 16); }
__device__ __forceinline__ float bf_hi(uint32_t u) { return __uint_as_float(u & 0xFFFF0000u); }
__device__ __forceinline__ float ex2(float x) { float r; asm("ex2.approx.ftz.f32 %0, %1;" : "=f"(r) : "f"(x)); return r; }
__device__ __forceinline__ void mma16816(float (&d)[4], uint32_t a0, uint32_t a1, uint32_t a2, uint32_t a3, uint32_t b0, uint32_t b1) {
  asm volatile("mma.sync.aligned.m16n8k16.row.col.f32.bf16.bf16.f32 {%0,%1,%2,%3},{%4,%5,%6,%7},{%8,%9},{%0,%1,%2,%3};"
               : "+f"(d[0]), "+f"(d[1]), "+f"(d[2]), "+f"(d[3]) : "r"(a0), "r"(a1), "r"(a2), "r"(a3), "r"(b0), "r"(b1));
}
__device__ __forceinline__ void wgmma_n64_bt(float (&d)[32], uint64_t da, uint64_t db, int sd) {
  asm volatile("{.reg .pred p; setp.ne.b32 p, %34, 0;\n"
  "wgmma.mma_async.sync.aligned.m64n64k16.f32.bf16.bf16 {%0, %1, %2, %3, %4, %5, %6, %7, %8, %9, %10, %11, %12, %13, %14, %15, %16, %17, %18, %19, %20, %21, %22, %23, %24, %25, %26, %27, %28, %29, %30, %31}, %32, %33, p, 1, 1, 0, 1;}\n"
  : "+f"(d[0]), "+f"(d[1]), "+f"(d[2]), "+f"(d[3]), "+f"(d[4]), "+f"(d[5]), "+f"(d[6]), "+f"(d[7]), "+f"(d[8]), "+f"(d[9]), "+f"(d[10]), "+f"(d[11]), "+f"(d[12]), "+f"(d[13]), "+f"(d[14]), "+f"(d[15]), "+f"(d[16]), "+f"(d[17]), "+f"(d[18]), "+f"(d[19]), "+f"(d[20]), "+f"(d[21]), "+f"(d[22]), "+f"(d[23]), "+f"(d[24]), "+f"(d[25]), "+f"(d[26]), "+f"(d[27]), "+f"(d[28]), "+f"(d[29]), "+f"(d[30]), "+f"(d[31]) : "l"(da), "l"(db), "r"(sd));
}
__device__ __forceinline__ void wgmma_n128_bt(float (&d)[64], uint64_t da, uint64_t db, int sd) {
  asm volatile("{.reg .pred p; setp.ne.b32 p, %66, 0;\n"
  "wgmma.mma_async.sync.aligned.m64n128k16.f32.bf16.bf16 {%0, %1, %2, %3, %4, %5, %6, %7, %8, %9, %10, %11, %12, %13, %14, %15, %16, %17, %18, %19, %20, %21, %22, %23, %24, %25, %26, %27, %28, %29, %30, %31, %32, %33, %34, %35, %36, %37, %38, %39, %40, %41, %42, %43, %44, %45, %46, %47, %48, %49, %50, %51, %52, %53, %54, %55, %56, %57, %58, %59, %60, %61, %62, %63}, %64, %65, p, 1, 1, 0, 1;}\n"
  : "+f"(d[0]), "+f"(d[1]), "+f"(d[2]), "+f"(d[3]), "+f"(d[4]), "+f"(d[5]), "+f"(d[6]), "+f"(d[7]), "+f"(d[8]), "+f"(d[9]), "+f"(d[10]), "+f"(d[11]), "+f"(d[12]), "+f"(d[13]), "+f"(d[14]), "+f"(d[15]), "+f"(d[16]), "+f"(d[17]), "+f"(d[18]), "+f"(d[19]), "+f"(d[20]), "+f"(d[21]), "+f"(d[22]), "+f"(d[23]), "+f"(d[24]), "+f"(d[25]), "+f"(d[26]), "+f"(d[27]), "+f"(d[28]), "+f"(d[29]), "+f"(d[30]), "+f"(d[31]), "+f"(d[32]), "+f"(d[33]), "+f"(d[34]), "+f"(d[35]), "+f"(d[36]), "+f"(d[37]), "+f"(d[38]), "+f"(d[39]), "+f"(d[40]), "+f"(d[41]), "+f"(d[42]), "+f"(d[43]), "+f"(d[44]), "+f"(d[45]), "+f"(d[46]), "+f"(d[47]), "+f"(d[48]), "+f"(d[49]), "+f"(d[50]), "+f"(d[51]), "+f"(d[52]), "+f"(d[53]), "+f"(d[54]), "+f"(d[55]), "+f"(d[56]), "+f"(d[57]), "+f"(d[58]), "+f"(d[59]), "+f"(d[60]), "+f"(d[61]), "+f"(d[62]), "+f"(d[63]) : "l"(da), "l"(db), "r"(sd));
}
__device__ __forceinline__ void wgmma_n176_bt(float (&d)[88], uint64_t da, uint64_t db, int sd) {
  asm volatile("{.reg .pred p; setp.ne.b32 p, %90, 0;\n"
  "wgmma.mma_async.sync.aligned.m64n176k16.f32.bf16.bf16 {%0, %1, %2, %3, %4, %5, %6, %7, %8, %9, %10, %11, %12, %13, %14, %15, %16, %17, %18, %19, %20, %21, %22, %23, %24, %25, %26, %27, %28, %29, %30, %31, %32, %33, %34, %35, %36, %37, %38, %39, %40, %41, %42, %43, %44, %45, %46, %47, %48, %49, %50, %51, %52, %53, %54, %55, %56, %57, %58, %59, %60, %61, %62, %63, %64, %65, %66, %67, %68, %69, %70, %71, %72, %73, %74, %75, %76, %77, %78, %79, %80, %81, %82, %83, %84, %85, %86, %87}, %88, %89, p, 1, 1, 0, 1;}\n"
  : "+f"(d[0]), "+f"(d[1]), "+f"(d[2]), "+f"(d[3]), "+f"(d[4]), "+f"(d[5]), "+f"(d[6]), "+f"(d[7]), "+f"(d[8]), "+f"(d[9]), "+f"(d[10]), "+f"(d[11]), "+f"(d[12]), "+f"(d[13]), "+f"(d[14]), "+f"(d[15]), "+f"(d[16]), "+f"(d[17]), "+f"(d[18]), "+f"(d[19]), "+f"(d[20]), "+f"(d[21]), "+f"(d[22]), "+f"(d[23]), "+f"(d[24]), "+f"(d[25]), "+f"(d[26]), "+f"(d[27]), "+f"(d[28]), "+f"(d[29]), "+f"(d[30]), "+f"(d[31]), "+f"(d[32]), "+f"(d[33]), "+f"(d[34]), "+f"(d[35]), "+f"(d[36]), "+f"(d[37]), "+f"(d[38]), "+f"(d[39]), "+f"(d[40]), "+f"(d[41]), "+f"(d[42]), "+f"(d[43]), "+f"(d[44]), "+f"(d[45]), "+f"(d[46]), "+f"(d[47]), "+f"(d[48]), "+f"(d[49]), "+f"(d[50]), "+f"(d[51]), "+f"(d[52]), "+f"(d[53]), "+f"(d[54]), "+f"(d[55]), "+f"(d[56]), "+f"(d[57]), "+f"(d[58]), "+f"(d[59]), "+f"(d[60]), "+f"(d[61]), "+f"(d[62]), "+f"(d[63]), "+f"(d[64]), "+f"(d[65]), "+f"(d[66]), "+f"(d[67]), "+f"(d[68]), "+f"(d[69]), "+f"(d[70]), "+f"(d[71]), "+f"(d[72]), "+f"(d[73]), "+f"(d[74]), "+f"(d[75]), "+f"(d[76]), "+f"(d[77]), "+f"(d[78]), "+f"(d[79]), "+f"(d[80]), "+f"(d[81]), "+f"(d[82]), "+f"(d[83]), "+f"(d[84]), "+f"(d[85]), "+f"(d[86]), "+f"(d[87]) : "l"(da), "l"(db), "r"(sd));
}
__device__ __forceinline__ void wgmma_qk_f16(float (&d)[32], uint64_t da, uint64_t db, int sd) {
  asm volatile("{.reg .pred p; setp.ne.b32 p, %34, 0;\n"
  "wgmma.mma_async.sync.aligned.m64n64k16.f32.f16.f16 {%0, %1, %2, %3, %4, %5, %6, %7, %8, %9, %10, %11, %12, %13, %14, %15, %16, %17, %18, %19, %20, %21, %22, %23, %24, %25, %26, %27, %28, %29, %30, %31}, %32, %33, p, 1, 1, 0, 0;}\n"
  : "+f"(d[0]), "+f"(d[1]), "+f"(d[2]), "+f"(d[3]), "+f"(d[4]), "+f"(d[5]), "+f"(d[6]), "+f"(d[7]), "+f"(d[8]), "+f"(d[9]), "+f"(d[10]), "+f"(d[11]), "+f"(d[12]), "+f"(d[13]), "+f"(d[14]), "+f"(d[15]), "+f"(d[16]), "+f"(d[17]), "+f"(d[18]), "+f"(d[19]), "+f"(d[20]), "+f"(d[21]), "+f"(d[22]), "+f"(d[23]), "+f"(d[24]), "+f"(d[25]), "+f"(d[26]), "+f"(d[27]), "+f"(d[28]), "+f"(d[29]), "+f"(d[30]), "+f"(d[31]) : "l"(da), "l"(db), "r"(sd));
}
__device__ __forceinline__ void wgmma_qk_bf16(float (&d)[32], uint64_t da, uint64_t db, int sd) {
  asm volatile("{.reg .pred p; setp.ne.b32 p, %34, 0;\n"
  "wgmma.mma_async.sync.aligned.m64n64k16.f32.bf16.bf16 {%0, %1, %2, %3, %4, %5, %6, %7, %8, %9, %10, %11, %12, %13, %14, %15, %16, %17, %18, %19, %20, %21, %22, %23, %24, %25, %26, %27, %28, %29, %30, %31}, %32, %33, p, 1, 1, 0, 0;}\n"
  : "+f"(d[0]), "+f"(d[1]), "+f"(d[2]), "+f"(d[3]), "+f"(d[4]), "+f"(d[5]), "+f"(d[6]), "+f"(d[7]), "+f"(d[8]), "+f"(d[9]), "+f"(d[10]), "+f"(d[11]), "+f"(d[12]), "+f"(d[13]), "+f"(d[14]), "+f"(d[15]), "+f"(d[16]), "+f"(d[17]), "+f"(d[18]), "+f"(d[19]), "+f"(d[20]), "+f"(d[21]), "+f"(d[22]), "+f"(d[23]), "+f"(d[24]), "+f"(d[25]), "+f"(d[26]), "+f"(d[27]), "+f"(d[28]), "+f"(d[29]), "+f"(d[30]), "+f"(d[31]) : "l"(da), "l"(db), "r"(sd));
}
__device__ __forceinline__ void wgmma_pv(float (&d)[12], uint32_t a0, uint32_t a1, uint32_t a2, uint32_t a3, uint64_t db) {
  asm volatile("wgmma.mma_async.sync.aligned.m64n24k16.f32.bf16.bf16 {%0, %1, %2, %3, %4, %5, %6, %7, %8, %9, %10, %11}, {%12, %13, %14, %15}, %16, 1, 1, 1, 1;\n"
  : "+f"(d[0]), "+f"(d[1]), "+f"(d[2]), "+f"(d[3]), "+f"(d[4]), "+f"(d[5]), "+f"(d[6]), "+f"(d[7]), "+f"(d[8]), "+f"(d[9]), "+f"(d[10]), "+f"(d[11]) : "r"(a0), "r"(a1), "r"(a2), "r"(a3), "l"(db));
}

#define PAT "IIMMIIIIMIIIIIMM"
__host__ __device__ constexpr char ptype(int i) { return PAT[i]; }
constexpr float INIT_L = 256.0f + 127.0f - 77.164f / 128.0f + 1.0f / 256.0f;
constexpr float INIT_I = 256.0f + 190.0f - 75.041f / 128.0f + 1.0f / 256.0f;
__host__ __device__ constexpr float initv(int i) { return ptype(i) == 'M' ? 0.0f : ptype(i) == 'L' ? INIT_L : INIT_I; }
__device__ __forceinline__ uint32_t exp_pair(char ty, float a, float b, uint32_t c1, uint32_t c2, uint32_t c3) {
  if (ty == 'M') return pack_bf16(ex2(a), ex2(b));
  uint32_t y = __byte_perm(__float_as_uint(a), __float_as_uint(b), 0x6521), m, e, r;
  if (ty == 'L') {
    asm("lop3.b32 %0, %1, 0x007F007F, %2, 0xEA;" : "=r"(m) : "r"(y), "r"(c1));
    asm("lop3.b32 %0, %1, 0x7F807F80, %2, 0xEA;" : "=r"(e) : "r"(y), "r"(c2));
  } else {
    asm("lop3.b32 %0, %1, 0x007F007F, %2, 0xEA;" : "=r"(m) : "r"(y), "r"(c3));
    e = y - m;
  }
  asm("fma.rn.bf16x2 %0, %1, %2, %3;" : "=r"(r) : "r"(y), "r"(m), "r"(e));
  return r;
}
template <int HF> __device__ __forceinline__ void exp_half(const float (&s)[32], uint32_t (&p)[8], uint32_t c1, uint32_t c2, uint32_t c3) {
#pragma unroll
  for (int i = HF * 8; i < HF * 8 + 8; i++) p[i - HF * 8] = exp_pair(ptype(i), s[2 * i], s[2 * i + 1], c1, c2, c3);
}

struct Params {
  CUtensorMap tx, twq, two, tw1, tw2;
  const __nv_bfloat16 *x, *wk, *wv, *wo, *w1, *w2;
  __nv_bfloat16* out;
  uint32_t c1, c2, c3;
};

__device__ __forceinline__ int f_start(int j) { int n4 = j >> 1; return 688 * (j & 1) + (n4 == 3 ? 512 : 176 * n4); }

__device__ __forceinline__ void load_w1(const Params& P, uint32_t sb, int j, int k) {
  uint32_t bar = sb + OFF_BAR + 8 * (B_W1F + k), dst = sb + (k % 7) * 24 * KB;
  int n0 = f_start(j);
#pragma unroll
  for (int a = 0; a < 3; a++) tma2d(dst + a * 8 * KB, &P.tw1, n0 + 64 * a, 64 * k, bar);
}

__device__ __forceinline__ void region_freed(const Params& P, uint32_t sb, int it) {
  uint32_t old;
  asm volatile("atom.acq_rel.cta.shared::cta.add.u32 %0, [%1], 1;" : "=r"(old) : "r"(sb + OFF_SC + 4 * (SC_FREE + it)) : "memory");
  if (old != 15) return;
  const int g = blockIdx.x >> 3, j = blockIdx.x & 7;
  const uint32_t bars = sb + OFF_BAR;
  uint32_t epoch;
  asm volatile("ld.shared.u32 %0, [%1];" : "=r"(epoch) : "r"(sb + OFF_SC + 4 * SC_EPOCH));
  if (it == 0) {
    flag_wait(C_AUX, (epoch + 1) * NAUX);
    mbar_expect(bars + 8 * B_W1F, 24 * KB + 704);
    load_w1(P, sb, j, 0);
    bulk_g2s(sb + OFF_CS, g_cs1 + f_start(j), 704, bars + 8 * B_W1F);
  } else if (it == 1) {
    flag_wait(C_O + g * 2, (epoch + 1) * 128);
    const uint8_t* src = g_o + (size_t)(g * 2) * 65536;
#pragma unroll
    for (int u = 0; u < 4; u++) mbar_expect(bars + 8 * (B_OF + u), 16 * KB);
#pragma unroll
    for (int k = 0; k < 8; k++) bulk_g2s(sb + (k < 3 ? 176 * KB + 8 * KB * k : 8 * KB * k), src + k * 8 * KB, 8 * KB, bars + 8 * (B_OF + (k >> 1)));
  } else {
    mbar_expect(bars + 8 * B_WOB, 40 * KB);
#pragma unroll
    for (int k = 3; k < 8; k++) tma2d(sb + 48 * KB + 8 * KB * k, &P.two, 64 * j, 64 * k, bars + 8 * B_WOB);
  }
}

__device__ __forceinline__ void publish_o(const float (&o)[12], int t, int wg) {
  const int lane = threadIdx.x & 31, warp = (threadIdx.x >> 5) & 3, g = blockIdx.x >> 3, j = blockIdx.x & 7;
  const float i0 = __fdividef(1.0f, o[8]), i1 = __fdividef(1.0f, o[10]);
  uint32_t* dst = (uint32_t*)(g_o + (size_t)(g * 2 + t) * 65536 + (8 * j + 2 * wg) * 1024 + warp * 256 + lane * 4);
  dst[0] = pack_bf16(o[0] * i0, o[1] * i0);
  dst[32] = pack_bf16(o[2] * i1, o[3] * i1);
  dst[256] = pack_bf16(o[4] * i0, o[5] * i0);
  dst[288] = pack_bf16(o[6] * i1, o[7] * i1);
  __syncwarp();
  if (lane == 0) flag_add(C_O + g * 2 + t);
}

__device__ __forceinline__ void attention_fast(const Params& P, uint32_t sb, int wg) {
  uint32_t c1 = P.c1, c2 = P.c2, c3 = P.c3;
  asm volatile("" : "+r"(c1), "+r"(c2), "+r"(c3));
#pragma unroll 1
  for (int t = 0; t < 2; t++) {
    float o[12], sA[32], sB[32];
    uint32_t pX[8], pY[8];
    const uint64_t dQ = mkdesc(sb + OFF_Q + (t * 4 + wg) * 2048, 1024, 128);
    uint64_t dK = mkdesc(sb, 4096, 128), dV = mkdesc(sb + 8192, 128, 4096);
#pragma unroll
    for (int i = 0; i < 12; i++) o[i] = 0.f;
#pragma unroll
    for (int i = 0; i < 16; i++) { sA[2 * i] = sA[2 * i + 1] = sB[2 * i] = sB[2 * i + 1] = initv(i); }
    pin(o); pin(sA); pin(sB);
    wg_fence();
    wgmma_qk_f16(sA, dQ, dK, 1);
    wgmma_qk_f16(sB, dQ, dK + 64, 1);
    wg_commit();
    wg_wait<0>();
#pragma unroll 1
    for (int it = 0; it < 4; it++) {
      pin(sA); pin(sB);
#pragma unroll
      for (int j = 0; j < 8; j++) {
        float(&s)[32] = (j & 1) ? sB : sA;
        const int voff = (j >> 2) * (CHB / 16) + (j & 3) * 64, koff = ((j + 2) >> 2) * (CHB / 16) + ((j + 2) & 3) * 64;
        if (j > 0) wg_wait<1>();
        pin(s); pin(pX);
        exp_half<0>(s, pX, c1, c2, c3);
        pin(pX);
        wg_fence();
        wgmma_pv(o, pX[0], pX[1], pX[2], pX[3], dV + voff);
        wgmma_pv(o, pX[4], pX[5], pX[6], pX[7], dV + voff + 16);
        wg_commit();
        if (j > 0) wg_wait<1>();
        pin(pY);
        exp_half<1>(s, pY, c1, c2, c3);
        pin(pY);
        wg_fence();
        wgmma_pv(o, pY[0], pY[1], pY[2], pY[3], dV + voff + 32);
        wgmma_pv(o, pY[4], pY[5], pY[6], pY[7], dV + voff + 48);
        wgmma_qk_f16(s, dQ, dK + koff, 1);
        wg_commit();
      }
      dK += 2 * (CHB / 16); dV += 2 * (CHB / 16);
      wg_wait<0>();
      if (t == 0) { if (it == 0) mbar_wait(sb + OFF_BAR + 8 * B_KV1, 0); }
      else if (it < 3) { if ((threadIdx.x & 31) == 0) region_freed(P, sb, it); __syncwarp(); }
    }
    pin(o); pin(pX); pin(pY);
    publish_o(o, t, wg);
  }
}

__device__ __forceinline__ void attention_safe(const Params& P, uint32_t sb, int wg) {
#pragma unroll 1
  for (int t = 0; t < 2; t++) {
    float o[12], s[32], m0 = -INFINITY, m1 = -INFINITY;
    uint32_t p[16];
    const uint64_t dQ = mkdesc(sb + OFF_Q + (t * 4 + wg) * 2048, 1024, 128);
#pragma unroll
    for (int i = 0; i < 12; i++) o[i] = 0.f;
#pragma unroll
    for (int i = 0; i < 32; i++) s[i] = 0.f;
#pragma unroll 1
    for (int j = 0; j < 32; j++) {
      const uint32_t base = sb + (j >> 2) * CHB + (j & 3) * 1024;
      pin(s);
      wg_fence();
      wgmma_qk_bf16(s, dQ, mkdesc(base, 4096, 128), 0);
      wg_commit();
      wg_wait<0>();
      pin(s);
      float n0 = m0, n1 = m1;
#pragma unroll
      for (int i = 0; i < 16; i++) {
        const uint32_t r = pack_bf16(s[2 * i], s[2 * i + 1]);
        s[2 * i] = bf_lo(r); s[2 * i + 1] = bf_hi(r);
        if (i & 1) n1 = fmaxf(n1, fmaxf(s[2 * i], s[2 * i + 1])); else n0 = fmaxf(n0, fmaxf(s[2 * i], s[2 * i + 1]));
      }
      n0 = fmaxf(n0, __shfl_xor_sync(~0u, n0, 1)); n0 = fmaxf(n0, __shfl_xor_sync(~0u, n0, 2));
      n1 = fmaxf(n1, __shfl_xor_sync(~0u, n1, 1)); n1 = fmaxf(n1, __shfl_xor_sync(~0u, n1, 2));
      const float r0 = ex2((m0 - n0) * QK_SCALE_LOG2), r1 = ex2((m1 - n1) * QK_SCALE_LOG2);
      m0 = n0; m1 = n1;
#pragma unroll
      for (int i = 0; i < 12; i++) o[i] *= (i & 2) ? r1 : r0;
#pragma unroll
      for (int i = 0; i < 16; i++) {
        const float mm = (i & 1) ? m1 : m0;
        p[i] = pack_bf16(ex2((s[2 * i] - mm) * QK_SCALE_LOG2), ex2((s[2 * i + 1] - mm) * QK_SCALE_LOG2));
      }
      pin(o); pin(p);
      wg_fence();
      const uint64_t dV = mkdesc(base + 8192, 128, 4096);
#pragma unroll
      for (int k = 0; k < 4; k++) wgmma_pv(o, p[4 * k], p[4 * k + 1], p[4 * k + 2], p[4 * k + 3], dV + 16 * k);
      wg_commit();
      wg_wait<0>();
      pin(o); pin(p);
      if (t == 1 && (j & 7) == 7 && j < 24) { if ((threadIdx.x & 31) == 0) region_freed(P, sb, j >> 3); __syncwarp(); }
    }
    publish_o(o, t, wg);
  }
}

__device__ __forceinline__ void aux_cta(const Params& P, uint8_t* smem) {
  const int a = blockIdx.x - NMAIN, tid = threadIdx.x;
  __nanosleep(1500);
  if (tid < 64) {
    l2_prefetch((const uint8_t*)P.wo + (size_t)(a * 64 + tid) * 2048, 2048);
    l2_prefetch((const uint8_t*)P.w2 + (size_t)(a * 64 + tid) * 5504, 5504);
  }
  float* red = (float*)smem;
  const int cg = tid % 43, rg = tid / 43;
  if (rg < 11) {
    float acc[8];
#pragma unroll
    for (int i = 0; i < 8; i++) acc[i] = 0.f;
#pragma unroll 4
    for (int r = rg; r < D_; r += 11) {
      const uint4 v = __ldg((const uint4*)(P.w1 + (size_t)r * F_ + a * 344 + cg * 8));
      acc[0] += bf_lo(v.x); acc[1] += bf_hi(v.x); acc[2] += bf_lo(v.y); acc[3] += bf_hi(v.y);
      acc[4] += bf_lo(v.z); acc[5] += bf_hi(v.z); acc[6] += bf_lo(v.w); acc[7] += bf_hi(v.w);
    }
#pragma unroll
    for (int i = 0; i < 8; i++) red[rg * 344 + cg * 8 + i] = acc[i];
  }
  __syncthreads();
  if (tid < 344) {
    float sum = 0.f;
#pragma unroll
    for (int r = 0; r < 11; r++) sum += red[r * 344 + tid];
    g_cs1[a * 344 + tid] = sum;
  }
  __syncthreads();
  if (tid == 0) { flag_add(C_AUX); flag_add(C_DONE); }
}

__device__ __forceinline__ void kv_path(const Params& P, uint8_t* smem, const uint4 (&xr)[4], const uint32_t (&wkr)[16], const uint32_t (&wvr)[16]) {
  const int t = threadIdx.x - 256, w = t >> 5, lane = t & 31, g8 = lane >> 2, c = lane & 3;
  float dk0[4] = {0, 0, 0, 0}, dk1[4] = {0, 0, 0, 0}, dv0[4] = {0, 0, 0, 0}, dv1[4] = {0, 0, 0, 0};
  float ck0[4] = {0, 0, 0, 0}, ck1[4] = {0, 0, 0, 0}, cv0[4] = {0, 0, 0, 0}, cv1[4] = {0, 0, 0, 0};
  const uint32_t one = 0x3F803F80u;
  float s0 = 0, q0 = 0, s1 = 0, q1 = 0;
#pragma unroll
  for (int hb = 0; hb < 2; hb++) {
    const uint32_t xa[4] = {xr[2 * hb].x, xr[2 * hb].y, xr[2 * hb].z, xr[2 * hb].w};
    const uint32_t xb[4] = {xr[2 * hb + 1].x, xr[2 * hb + 1].y, xr[2 * hb + 1].z, xr[2 * hb + 1].w};
#pragma unroll
    for (int s = 0; s < 2; s++) {
      const int kk = hb * 8 + 4 * s;
      const uint32_t ke0 = __byte_perm(wkr[kk], wkr[kk + 1], 0x5410), ke1 = __byte_perm(wkr[kk + 2], wkr[kk + 3], 0x5410);
      const uint32_t ko0 = __byte_perm(wkr[kk], wkr[kk + 1], 0x7632), ko1 = __byte_perm(wkr[kk + 2], wkr[kk + 3], 0x7632);
      const uint32_t ve0 = __byte_perm(wvr[kk], wvr[kk + 1], 0x5410), ve1 = __byte_perm(wvr[kk + 2], wvr[kk + 3], 0x5410);
      const uint32_t vo0 = __byte_perm(wvr[kk], wvr[kk + 1], 0x7632), vo1 = __byte_perm(wvr[kk + 2], wvr[kk + 3], 0x7632);
      mma16816(dk0, xa[2 * s], xb[2 * s], xa[2 * s + 1], xb[2 * s + 1], ke0, ke1);
      mma16816(dk1, xa[2 * s], xb[2 * s], xa[2 * s + 1], xb[2 * s + 1], ko0, ko1);
      mma16816(dv0, xa[2 * s], xb[2 * s], xa[2 * s + 1], xb[2 * s + 1], ve0, ve1);
      mma16816(dv1, xa[2 * s], xb[2 * s], xa[2 * s + 1], xb[2 * s + 1], vo0, vo1);
      mma16816(ck0, one, one, one, one, ke0, ke1);
      mma16816(ck1, one, one, one, one, ko0, ko1);
      mma16816(cv0, one, one, one, one, ve0, ve1);
      mma16816(cv1, one, one, one, one, vo0, vo1);
    }
#pragma unroll
    for (int i = 0; i < 4; i++) {
      float a = bf_lo(xa[i]), b = bf_hi(xa[i]); s0 += a + b; q0 += a * a + b * b;
      a = bf_lo(xb[i]); b = bf_hi(xb[i]); s1 += a + b; q1 += a * a + b * b;
    }
  }
  s0 += __shfl_xor_sync(~0u, s0, 1); q0 += __shfl_xor_sync(~0u, q0, 1); s1 += __shfl_xor_sync(~0u, s1, 1); q1 += __shfl_xor_sync(~0u, q1, 1);
  s0 += __shfl_xor_sync(~0u, s0, 2); q0 += __shfl_xor_sync(~0u, q0, 2); s1 += __shfl_xor_sync(~0u, s1, 2); q1 += __shfl_xor_sync(~0u, q1, 2);
  float* part = (float*)(smem + OFF_STG);
  float2* pst = (float2*)(smem + OFF_STG + 18 * KB);
  float* kf = (float*)(smem + OFF_STG + 20 * KB);
  float* pw = part + w * 17 * 32;
  *(float4*)(pw + g8 * 32 + 4 * c) = make_float4(dk0[0], dk1[0], dk0[1], dk1[1]);
  *(float4*)(pw + g8 * 32 + 16 + 4 * c) = make_float4(dv0[0], dv1[0], dv0[1], dv1[1]);
  *(float4*)(pw + (g8 + 8) * 32 + 4 * c) = make_float4(dk0[2], dk1[2], dk0[3], dk1[3]);
  *(float4*)(pw + (g8 + 8) * 32 + 16 + 4 * c) = make_float4(dv0[2], dv1[2], dv0[3], dv1[3]);
  if (g8 == 0) {
    *(float4*)(pw + 16 * 32 + 4 * c) = make_float4(ck0[0], ck1[0], ck0[1], ck1[1]);
    *(float4*)(pw + 16 * 32 + 16 + 4 * c) = make_float4(cv0[0], cv1[0], cv0[1], cv1[1]);
  }
  if (c == 0) { pst[w * 16 + g8] = make_float2(s0, q0); pst[w * 16 + g8 + 8] = make_float2(s1, q1); }
  bar_sync(1, 256);
  const int row = t >> 4, cp = t & 15;
  float ax = 0, ay = 0, cx = 0, cy = 0, sm = 0, sq = 0;
#pragma unroll
  for (int i = 0; i < 8; i++) {
    const float2 a = *(const float2*)(part + (i * 17 + row) * 32 + 2 * cp), cc = *(const float2*)(part + (i * 17 + 16) * 32 + 2 * cp), st = pst[i * 16 + row];
    ax += a.x; ay += a.y; cx += cc.x; cy += cc.y; sm += st.x; sq += st.y;
  }
  const float mean = sm * (1.0f / D_), rstd = rsqrtf(fmaxf(sq * (1.0f / D_) - mean * mean, 0.f) + LN_EPS);
  const uint32_t val = pack_bf16(rstd * (ax - mean * cx), rstd * (ay - mean * cy));
  const int cta = blockIdx.x, slot = (2 * row + (cta >> 6)) * 64 + (cta & 63);
  const int inner = ((cp >> 2) & 1) * 4096 + (slot & 255) * 16 + (cp & 3) * 4;
  const float v0 = bf_lo(val), v1 = bf_hi(val);
  float red;
  if (cp < 8) {
    *(uint32_t*)(g_kp + (slot >> 8) * 8192 + inner) = val;
    const float k0 = v0 * QK_SCALE_LOG2, k1 = v1 * QK_SCALE_LOG2;
    *(float2*)(kf + row * 16 + 2 * cp) = make_float2(k0, k1);
    red = k0 * k0 + k1 * k1;
  } else {
    *(uint32_t*)(g_kv + (slot >> 8) * 16384 + 8192 + inner) = val;
    red = v0 * v0 + v1 * v1;
  }
  red += __shfl_xor_sync(~0u, red, 1); red += __shfl_xor_sync(~0u, red, 2); red += __shfl_xor_sync(~0u, red, 4);
  float* nrm = kf + 256;
  if ((cp & 7) == 0) nrm[row * 2 + (cp >> 3)] = red;
  if (cp == 0) g_st1[cta * 16 + row] = make_float2(mean, rstd);
  bar_sync(1, 256);
  if (w == 0) {
    if (lane < 16) {
      float kv[16];
#pragma unroll
      for (int r = 0; r < 16; r++) kv[r] = kf[r * 16 + lane];
      float run = 0.f;
#pragma unroll
      for (int r = 0; r < 16; r++) {
        const __half d = __float2half_rn(kv[r] - run);
        run += __half2float(d);
        const int sl = (2 * r + (cta >> 6)) * 64 + (cta & 63);
        *(__half*)(g_kv + (sl >> 8) * 16384 + (lane >> 3) * 4096 + (sl & 255) * 16 + (lane & 7) * 2) = d;
      }
    }
    uint32_t u = __float_as_uint(nrm[lane]);
#pragma unroll
    for (int o = 2; o < 32; o <<= 1) u = max(u, __shfl_xor_sync(~0u, u, o));
    const uint32_t u1 = __shfl_sync(~0u, u, 1);
    if (lane == 0) g_kmax[cta] = make_float2(__uint_as_float(u), __uint_as_float(u1));
    __syncwarp();
    if (lane == 0) flag_add(C_KV);
  }
}

__device__ __forceinline__ void post_chain(const Params& P, uint8_t* smem, uint32_t sb, int hf) {
  const int tid = threadIdx.x & 127, warp = tid >> 5, lane = tid & 31, g8 = lane >> 2, c = lane & 3;
  const int g = blockIdx.x >> 3, j = blockIdx.x & 7, gh = g * 2 + hf;
  const uint32_t bars = sb + OFF_BAR, ring = sb + OFF_RING + hf * 24 * KB;
  const int row0 = g * 128 + hf * 64 + warp * 16 + g8;
  uint8_t* himg = g_h + (size_t)gh * 65536 + 8 * j * 1024 + warp * 256 + lane * 4;
  {
    uint32_t xr[16];
    const uint32_t* xp = (const uint32_t*)(P.x + (size_t)row0 * D_ + 64 * j + 2 * c);
#pragma unroll
    for (int b = 0; b < 8; b++) { xr[2 * b] = __ldg(xp + 4 * b); xr[2 * b + 1] = __ldg(xp + 8 * 256 + 4 * b); }
    float acc[32];
#pragma unroll
    for (int i = 0; i < 32; i++) acc[i] = 0.f;
    pin(acc);
    mbar_wait(bars + 8 * B_WOA, 0);
    mbar_wait(bars + 8 * B_WOB, 0);
#pragma unroll
    for (int k = 0; k < 8; k++) {
      if ((k & 1) == 0) mbar_wait(bars + 8 * (B_OF + hf * 4 + (k >> 1)), 0);
      const uint32_t aoff = hf ? (k < 7 ? 120 * KB + 8 * KB * k : 112 * KB) : (k < 3 ? 176 * KB + 8 * KB * k : 8 * KB * k);
      const uint32_t boff = k < 3 ? 200 * KB + 8 * KB * k : 48 * KB + 8 * KB * k;
      const uint64_t da = mkdesc(sb + aoff, 1024, 128), db = mkdesc(sb + boff, 8192, 1024, 1);
      wg_fence();
#pragma unroll
      for (int s = 0; s < 4; s++) wgmma_n64_bt(acc, da + 128 * s, db + 128 * s, 1);
      wg_commit();
    }
    wg_wait<0>();
    pin(acc);
    if (lane == 0) mbar_arrive(bars + 8 * (B_PDONE + hf));
    float s0 = 0, q0 = 0, s1 = 0, q1 = 0;
#pragma unroll
    for (int b = 0; b < 8; b++) {
      const uint32_t h0 = pack_bf16(acc[4 * b] + bf_lo(xr[2 * b]), acc[4 * b + 1] + bf_hi(xr[2 * b]));
      const uint32_t h1 = pack_bf16(acc[4 * b + 2] + bf_lo(xr[2 * b + 1]), acc[4 * b + 3] + bf_hi(xr[2 * b + 1]));
      *(uint32_t*)(himg + b * 1024) = h0;
      *(uint32_t*)(himg + b * 1024 + 128) = h1;
      float a = bf_lo(h0), bb = bf_hi(h0); s0 += a + bb; q0 += a * a + bb * bb;
      a = bf_lo(h1); bb = bf_hi(h1); s1 += a + bb; q1 += a * a + bb * bb;
    }
    s0 += __shfl_xor_sync(~0u, s0, 1); q0 += __shfl_xor_sync(~0u, q0, 1); s1 += __shfl_xor_sync(~0u, s1, 1); q1 += __shfl_xor_sync(~0u, q1, 1);
    s0 += __shfl_xor_sync(~0u, s0, 2); q0 += __shfl_xor_sync(~0u, q0, 2); s1 += __shfl_xor_sync(~0u, s1, 2); q1 += __shfl_xor_sync(~0u, q1, 2);
    if (c == 0) { g_st2[(gh * 8 + j) * 64 + warp * 16 + g8] = make_float2(s0, q0); g_st2[(gh * 8 + j) * 64 + warp * 16 + g8 + 8] = make_float2(s1, q1); }
    __syncwarp();
    if (lane == 0) flag_add(C_H + gh);
  }
  if (tid == 0) TSTAMP(8 + hf * 8);
  {
    float acc[88];
#pragma unroll
    for (int i = 0; i < 88; i++) acc[i] = 0.f;
    pin(acc);
    float mean0, rstd0, mean1, rstd1;
#pragma unroll
    for (int k = 0; k < 8; k++) {
      mbar_wait(bars + 8 * (B_RF + hf * 3 + k % 3), (k / 3) & 1);
      mbar_wait(bars + 8 * (B_W1F + k), 0);
      const uint64_t da = mkdesc(ring + (k % 3) * 8 * KB, 1024, 128), db = mkdesc(sb + (k % 7) * 24 * KB, 8192, 1024, 1);
      wg_fence();
#pragma unroll
      for (int s = 0; s < 4; s++) wgmma_n176_bt(acc, da + 128 * s, db + 128 * s, 1);
      wg_commit();
      if (k == 0) {
        const float2* sp = g_st2 + (gh * 8 + 2 * c) * 64 + warp * 16 + g8;
        const float2 a0 = __ldcg(sp), a1 = __ldcg(sp + 64), b0 = __ldcg(sp + 8), b1 = __ldcg(sp + 72);
        float s0 = a0.x + a1.x, q0 = a0.y + a1.y, s1 = b0.x + b1.x, q1 = b0.y + b1.y;
        s0 += __shfl_xor_sync(~0u, s0, 1); q0 += __shfl_xor_sync(~0u, q0, 1); s1 += __shfl_xor_sync(~0u, s1, 1); q1 += __shfl_xor_sync(~0u, q1, 1);
        s0 += __shfl_xor_sync(~0u, s0, 2); q0 += __shfl_xor_sync(~0u, q0, 2); s1 += __shfl_xor_sync(~0u, s1, 2); q1 += __shfl_xor_sync(~0u, q1, 2);
        mean0 = s0 * (1.0f / D_); rstd0 = rsqrtf(fmaxf(q0 * (1.0f / D_) - mean0 * mean0, 0.f) + LN_EPS);
        mean1 = s1 * (1.0f / D_); rstd1 = rsqrtf(fmaxf(q1 * (1.0f / D_) - mean1 * mean1, 0.f) + LN_EPS);
      } else {
        wg_wait<1>();
        if (lane == 0) { mbar_arrive(bars + 8 * (B_RE + hf * 3 + (k - 1) % 3)); mbar_arrive(bars + 8 * (B_W1E + k - 1)); }
      }
    }
    wg_wait<0>();
    pin(acc);
    if (lane == 0) { mbar_arrive(bars + 8 * (B_RE + hf * 3 + 7 % 3)); mbar_arrive(bars + 8 * (B_W1E + 7)); }
    if (tid == 0) TSTAMP(9 + hf * 8);
    const float2* cs = (const float2*)(smem + OFF_CS) + c;
    uint8_t* dst = g_hh + (size_t)gh * 172 * 1024 + (f_start(j) >> 3) * 1024 + warp * 256 + lane * 4;
    const float hr0 = 0.5f * rstd0, hr1 = 0.5f * rstd1;
#pragma unroll
    for (int b = 0; b < 22; b++) {
      const float2 cc = cs[4 * b];
      float v[4] = {hr0 * (acc[4 * b] - mean0 * cc.x), hr0 * (acc[4 * b + 1] - mean0 * cc.y),
                    hr1 * (acc[4 * b + 2] - mean1 * cc.x), hr1 * (acc[4 * b + 3] - mean1 * cc.y)};
#pragma unroll
      for (int i = 0; i < 4; i++) {
        float th; asm("tanh.approx.f32 %0, %1;" : "=f"(th) : "f"(v[i]));
        v[i] = fmaf(v[i], th, v[i]);
      }
      *(uint32_t*)(dst + b * 1024) = pack_bf16(v[0], v[1]);
      *(uint32_t*)(dst + b * 1024 + 128) = pack_bf16(v[2], v[3]);
    }
    __syncwarp();
    if (lane == 0) flag_add(C_HH + gh * 2 + (j & 1));
  }
  if (tid == 0) TSTAMP(10 + hf * 8);
  {
    float acc[64];
#pragma unroll
    for (int i = 0; i < 64; i++) acc[i] = 0.f;
    pin(acc);
    uint32_t hr[16];
#pragma unroll
    for (int b = 0; b < 8; b++) { hr[2 * b] = __ldcg((const uint32_t*)(himg + b * 1024)); hr[2 * b + 1] = __ldcg((const uint32_t*)(himg + b * 1024 + 128)); }
#pragma unroll
    for (int i = 0; i < 11; i++) {
      const int r = 8 + i;
      mbar_wait(bars + 8 * (B_RF + hf * 3 + r % 3), (r / 3) & 1);
      mbar_wait(bars + 8 * (B_W2F + i), 0);
      const uint64_t da = mkdesc(ring + (r % 3) * 8 * KB, 1024, 128);
      const uint64_t db = i < 9 ? mkdesc(sb + 24 * KB + 16 * KB * i, 8192, 1024, 1) : i == 9 ? mkdesc(sb, 8192, 1024, 1) : mkdesc(sb + 16 * KB, 152 * KB, 1024, 1);
      wg_fence();
#pragma unroll
      for (int s = 0; s < (i == 10 ? 3 : 4); s++) wgmma_n128_bt(acc, da + 128 * s, db + 128 * s, 1);
      wg_commit();
      if (i > 0 && i < 9) {
        wg_wait<1>();
        if (lane == 0) mbar_arrive(bars + 8 * (B_RE + hf * 3 + (r - 1) % 3));
      }
    }
    wg_wait<0>();
    pin(acc);
    if (tid == 0) TSTAMP(11 + hf * 8);
    bar_sync(2 + hf, 128);
    const int kh = j & 1;
    float4* buf = (float4*)(smem + OFF_RING + hf * 24 * KB) + tid;
#pragma unroll
    for (int i = 0; i < 8; i++) {
      buf[i * 128] = kh ? make_float4(acc[4 * i], acc[4 * i + 1], acc[4 * i + 2], acc[4 * i + 3])
                        : make_float4(acc[32 + 4 * i], acc[33 + 4 * i], acc[34 + 4 * i], acc[35 + 4 * i]);
    }
    __syncwarp();
    uint32_t peer_bar, peer_buf;
    asm volatile("mapa.shared::cluster.u32 %0, %1, %2;" : "=r"(peer_bar) : "r"(bars + 8 * (B_RED + hf)), "r"(kh ^ 1));
    asm volatile("mapa.shared::cluster.u32 %0, %1, %2;" : "=r"(peer_buf) : "r"(ring + tid * 16), "r"(kh ^ 1));
    if (lane == 0) asm volatile("mbarrier.arrive.release.cluster.shared::cluster.b64 _, [%0];" ::"r"(peer_bar) : "memory");
    mbar_wait_cluster(bars + 8 * (B_RED + hf), 0);
    uint32_t* op = (uint32_t*)(P.out + (size_t)row0 * D_ + 64 * j + 2 * c);
#pragma unroll
    for (int i = 0; i < 8; i++) {
      float4 r;
      asm volatile("ld.shared::cluster.v4.f32 {%0,%1,%2,%3}, [%4];" : "=f"(r.x), "=f"(r.y), "=f"(r.z), "=f"(r.w) : "r"(peer_buf + i * 2048) : "memory");
      const float a0 = kh ? acc[32 + 4 * i] : acc[4 * i], a1 = kh ? acc[33 + 4 * i] : acc[4 * i + 1];
      const float a2 = kh ? acc[34 + 4 * i] : acc[4 * i + 2], a3 = kh ? acc[35 + 4 * i] : acc[4 * i + 3];
      op[4 * i] = pack_bf16(a0 + r.x + bf_lo(hr[2 * i]), a1 + r.y + bf_hi(hr[2 * i]));
      op[8 * 256 + 4 * i] = pack_bf16(a2 + r.z + bf_lo(hr[2 * i + 1]), a3 + r.w + bf_hi(hr[2 * i + 1]));
    }
    if (tid == 0) TSTAMP(12 + hf * 8);
  }
}

__device__ __forceinline__ void ring_producer(uint32_t sb, int hf, uint32_t epoch) {
  const int g = blockIdx.x >> 3, j = blockIdx.x & 7, gh = g * 2 + hf;
  const uint32_t bars = sb + OFF_BAR, ring = sb + OFF_RING + hf * 24 * KB;
  if (hf == 1) {
    mbar_wait(bars + 8 * B_ADONE, 0);
    flag_wait(C_O + gh, (epoch + 1) * 128);
    const uint8_t* src = g_o + (size_t)gh * 65536;
#pragma unroll
    for (int k = 0; k < 8; k++) {
      if ((k & 1) == 0) mbar_expect(bars + 8 * (B_OF + 4 + (k >> 1)), 16 * KB);
      bulk_g2s(sb + (k < 7 ? 120 * KB + 8 * KB * k : 112 * KB), src + k * 8 * KB, 8 * KB, bars + 8 * (B_OF + 4 + (k >> 1)));
    }
    mbar_wait(bars + 8 * B_PDONE, 0);
  }
  flag_wait(C_H + gh, (epoch + 1) * 32);
  const uint8_t* hsrc = g_h + (size_t)gh * 65536;
  const uint8_t* asrc = g_hh + (size_t)gh * 172 * 1024 + (j & 1) * 86 * 1024;
#pragma unroll 1
  for (int r = 0; r < 19; r++) {
    const int slot = r % 3;
    if (r == 8) flag_wait(C_HH + gh * 2 + (j & 1), (epoch + 1) * 16);
    if (r >= 3) mbar_wait(bars + 8 * (B_RE + hf * 3 + slot), ((r / 3) - 1) & 1);
    const uint32_t n = r == 18 ? 6 * KB : 8 * KB;
    mbar_expect(bars + 8 * (B_RF + hf * 3 + slot), n);
    bulk_g2s(ring + slot * 8 * KB, r < 8 ? hsrc + r * 8 * KB : asrc + (r - 8) * 8 * KB, n, bars + 8 * (B_RF + hf * 3 + slot));
  }
}

__device__ __forceinline__ void weight_producer(const Params& P, uint32_t sb) {
  const int j = blockIdx.x & 7;
  const uint32_t bars = sb + OFF_BAR;
#pragma unroll 1
  for (int k = 1; k < 8; k++) {
    if (k == 1) mbar_wait(bars + 8 * B_PDONE, 0);
    if (k == 3) mbar_wait(bars + 8 * (B_PDONE + 1), 0);
    if (k == 7) mbar_wait(bars + 8 * B_W1E, 0);
    mbar_expect(bars + 8 * (B_W1F + k), 24 * KB);
    load_w1(P, sb, j, k);
  }
  const int n0 = (j >> 1) * 128, k0 = (j & 1) * 688;
#pragma unroll 1
  for (int i = 0; i < 11; i++) {
    const int dep = i < 9 ? (24 + 16 * i + 15) / 24 : 7;
    mbar_wait(bars + 8 * (B_W1E + dep), 0);
    const uint32_t d0 = i < 9 ? 24 * KB + 16 * KB * i : i == 9 ? 0 : 16 * KB, d1 = i < 10 ? d0 + 8 * KB : 168 * KB;
    mbar_expect(bars + 8 * (B_W2F + i), 16 * KB);
    tma2d(sb + d0, &P.tw2, n0, k0 + 64 * i, bars + 8 * (B_W2F + i));
    tma2d(sb + d1, &P.tw2, n0 + 64, k0 + 64 * i, bars + 8 * (B_W2F + i));
  }
}

__global__ void __cluster_dims__(2, 1, 1) __launch_bounds__(512, 1) fused_block_kernel(const __grid_constant__ Params P) {
  extern __shared__ __align__(1024) uint8_t smem[];
  if (blockIdx.x >= NMAIN) { aux_cta(P, smem); return; }
  const uint32_t sb = s2u(smem), bars = sb + OFF_BAR;
  const int tid = threadIdx.x, lane = tid & 31, warp = (tid >> 5) & 3;
  const int wg = __shfl_sync(~0u, tid >> 7, 0);
  const int g = blockIdx.x >> 3, j = blockIdx.x & 7;
  uint32_t* sc = (uint32_t*)(smem + OFF_SC);
  if (tid == 0) {
    TSTAMP(0);
    for (int i = 0; i < B_NUM; i++) {
      int cnt = 1;
      if (i == B_ADONE) cnt = 16;
      else if (i == B_PDONE || i == B_PDONE + 1 || i >= B_RE) cnt = 4;
      else if (i >= B_W1E && i < B_W2F) cnt = 8;
      mbar_init(bars + 8 * i, cnt);
    }
    asm volatile("fence.mbarrier_init.release.cluster;" ::: "memory");
    fence_async_smem();
    for (int k = 0; k < 8; k++) {
      mbar_expect(bars + 8 * (B_XQ + k), 24 * KB);
      tma2d(sb + OFF_X + 16 * KB * k, &P.tx, 64 * k, 128 * g, bars + 8 * (B_XQ + k));
      tma2d(sb + OFF_WQ + 8 * KB * k, &P.twq, 64 * j, 64 * k, bars + 8 * (B_XQ + k));
    }
    sc[SC_QMAX] = 0; sc[SC_KMAX] = 0; sc[SC_VMAX] = 0; sc[SC_FREE] = 0; sc[SC_FREE + 1] = 0; sc[SC_FREE + 2] = 0;
  }
  float qacc[32];
  if (wg < 2) {
    __syncthreads();
#pragma unroll
    for (int i = 0; i < 32; i++) qacc[i] = 0.f;
    pin(qacc);
#pragma unroll
    for (int k = 0; k < 8; k++) {
      mbar_wait(bars + 8 * (B_XQ + k), 0);
      const uint64_t da = mkdesc(sb + OFF_X + 16 * KB * k + wg * 8 * KB, 16, 1024, 1), db = mkdesc(sb + OFF_WQ + 8 * KB * k, 8192, 1024, 1);
      wg_fence();
#pragma unroll
      for (int s = 0; s < 4; s++) wgmma_n64_bt(qacc, da + 2 * s, db + 128 * s, 1);
      wg_commit();
    }
    wg_wait<0>();
    pin(qacc);
    if (tid == 0) TSTAMP(1);
  } else {
    const int w = (tid - 256) >> 5, g8 = lane >> 2, c = lane & 3;
    uint4 xr[4];
    uint32_t wkr[16], wvr[16];
    const __nv_bfloat16* xp = P.x + (size_t)(blockIdx.x * 16 + g8) * D_ + 64 * w + 8 * c;
    xr[0] = __ldg((const uint4*)xp); xr[1] = __ldg((const uint4*)(xp + 8 * D_));
    xr[2] = __ldg((const uint4*)(xp + 32)); xr[3] = __ldg((const uint4*)(xp + 8 * D_ + 32));
#pragma unroll
    for (int i = 0; i < 16; i++) {
      const int k = 64 * w + (i >> 3) * 32 + 8 * c + (i & 7);
      wkr[i] = __ldg((const uint32_t*)(P.wk + k * 16 + 2 * g8));
      wvr[i] = __ldg((const uint32_t*)(P.wv + k * 16 + 2 * g8));
    }
    uint32_t done = 0;
    if (tid == 511) done = *(volatile unsigned int*)&g_cnt[C_DONE * CNT_STRIDE];
    __syncthreads();
    kv_path(P, smem, xr, wkr, wvr);
    if (tid == 256) TSTAMP(2);
    if (tid == 511) sc[SC_EPOCH] = done / NCTA;
    const int t = tid - 256, cgp = t & 7, rg = t >> 3;
    float cs[8];
#pragma unroll
    for (int i = 0; i < 8; i++) cs[i] = 0.f;
#pragma unroll
    for (int k = 0; k < 8; k++) {
      mbar_wait(bars + 8 * (B_XQ + k), 0);
#pragma unroll
      for (int h = 0; h < 2; h++) {
        const int r = rg + 32 * h;
        const uint4 v = *(const uint4*)(smem + OFF_WQ + 8 * KB * k + r * 128 + ((cgp ^ (r & 7)) << 4));
        cs[0] += bf_lo(v.x); cs[1] += bf_hi(v.x); cs[2] += bf_lo(v.y); cs[3] += bf_hi(v.y);
        cs[4] += bf_lo(v.z); cs[5] += bf_hi(v.z); cs[6] += bf_lo(v.w); cs[7] += bf_hi(v.w);
      }
    }
#pragma unroll
    for (int i = 0; i < 8; i++) { cs[i] += __shfl_xor_sync(~0u, cs[i], 8); cs[i] += __shfl_xor_sync(~0u, cs[i], 16); }
    float* cpart = (float*)(smem + OFF_STG + 24 * KB);
    if (lane < 8) {
      *(float4*)(cpart + w * 64 + lane * 8) = make_float4(cs[0], cs[1], cs[2], cs[3]);
      *(float4*)(cpart + w * 64 + lane * 8 + 4) = make_float4(cs[4], cs[5], cs[6], cs[7]);
    }
    bar_sync(1, 256);
    if (t < 64) {
      float sum = 0.f;
#pragma unroll
      for (int i = 0; i < 8; i++) sum += cpart[i * 64 + t];
      ((float*)(smem + OFF_CS))[t] = sum;
    }
  }
  __syncthreads();
  if (tid == 511) {
    flag_wait(C_KV, (sc[SC_EPOCH] + 1) * NMAIN);
    TSTAMP(3);
    mbar_expect(bars + 8 * B_KV0, 3 * 16 * KB);
    for (int c = 0; c < 3; c++) bulk_g2s(sb + c * CHB, g_kv + c * 16384, 16384, bars + 8 * B_KV0);
    mbar_expect(bars + 8 * B_KV1, 5 * 16 * KB);
    for (int c = 3; c < 8; c++) bulk_g2s(sb + c * CHB, g_kv + c * 16384, 16384, bars + 8 * B_KV1);
    mbar_expect(bars + 8 * B_WOA, 24 * KB);
    for (int k = 0; k < 3; k++) tma2d(sb + 200 * KB + 8 * KB * k, &P.two, 64 * j, 64 * k, bars + 8 * B_WOA);
  }
#pragma unroll
  for (int i = 0; i < 4; i++) {
    const int e = tid + 512 * i;
    *(uint4*)(smem + (e >> 8) * CHB + 16384 + (e & 255) * 16) = make_uint4(0x3F803F80u, 0x3F803F80u, 0x3F803F80u, 0x3F803F80u);
  }
  __syncthreads();
  uint32_t qb[16];
  uint8_t* qdst = smem + OFF_Q + wg * 8192 + warp * 256 + lane * 4;
  if (wg < 2) {
    const int r0 = g * 128 + wg * 64 + warp * 16 + (lane >> 2);
    const float2 st0 = __ldcg(&g_st1[r0]), st1 = __ldcg(&g_st1[r0 + 8]);
    const float2* cs = (const float2*)(smem + OFF_CS) + (lane & 3);
    uint32_t nanb = 0;
#pragma unroll
    for (int h = 0; h < 4; h++) {
      float n0 = 0.f, n1 = 0.f;
#pragma unroll
      for (int b = 2 * h; b < 2 * h + 2; b++) {
        const float2 cc = cs[4 * b];
        qb[2 * b] = pack_bf16(st0.y * (qacc[4 * b] - st0.x * cc.x), st0.y * (qacc[4 * b + 1] - st0.x * cc.y));
        qb[2 * b + 1] = pack_bf16(st1.y * (qacc[4 * b + 2] - st1.x * cc.x), st1.y * (qacc[4 * b + 3] - st1.x * cc.y));
        const float a0 = bf_lo(qb[2 * b]), a1 = bf_hi(qb[2 * b]), b0 = bf_lo(qb[2 * b + 1]), b1 = bf_hi(qb[2 * b + 1]);
        *(uint32_t*)(qdst + b * 1024) = pack_f16(a0, a1);
        *(uint32_t*)(qdst + b * 1024 + 128) = pack_f16(b0, b1);
        n0 += a0 * a0 + a1 * a1; n1 += b0 * b0 + b1 * b1;
      }
      n0 += __shfl_xor_sync(~0u, n0, 1); n1 += __shfl_xor_sync(~0u, n1, 1);
      n0 += __shfl_xor_sync(~0u, n0, 2); n1 += __shfl_xor_sync(~0u, n1, 2);
      nanb = max(nanb, max(__float_as_uint(n0), __float_as_uint(n1)));
    }
    nanb = __reduce_max_sync(~0u, nanb);
    if (lane == 0) atomicMax(&sc[SC_QMAX], nanb);
  } else if (wg == 2) {
    const float2 km = __ldcg(&g_kmax[tid - 256]);
    const uint32_t a = __reduce_max_sync(~0u, __float_as_uint(km.x)), b = __reduce_max_sync(~0u, __float_as_uint(km.y));
    if (lane == 0) { atomicMax(&sc[SC_KMAX], a); atomicMax(&sc[SC_VMAX], b); }
  }
  fence_async_smem();
  __syncthreads();
  const float q2 = __uint_as_float(sc[SC_QMAX]), k2 = __uint_as_float(sc[SC_KMAX]), v2 = __uint_as_float(sc[SC_VMAX]);
  const bool fast = (q2 * k2 <= 56.f * 56.f) && (q2 <= 1048576.f) && (k2 <= 1048576.f) && (v2 <= 1e24f);
  mbar_wait(bars + 8 * B_KV0, 0);
  if (tid == 0) TSTAMP(4);
  if (fast) {
    attention_fast(P, sb, wg);
  } else {
    mbar_wait(bars + 8 * B_KV1, 0);
    if (wg < 2) {
#pragma unroll
      for (int b = 0; b < 8; b++) { *(uint32_t*)(qdst + b * 1024) = qb[2 * b]; *(uint32_t*)(qdst + b * 1024 + 128) = qb[2 * b + 1]; }
    }
    for (int e = tid; e < 4096; e += 512) *(uint4*)(smem + (e >> 9) * CHB + (e & 511) * 16) = __ldcg((const uint4*)g_kp + e);
    fence_async_smem();
    __syncthreads();
    attention_safe(P, sb, wg);
  }
  if (lane == 0) mbar_arrive(bars + 8 * B_ADONE);
  if (tid == 0) TSTAMP(5);
  if ((wg & 1) == 0) {
    post_chain(P, smem, sb, wg >> 1);
  } else if (lane == 0) {
    if (warp == 0) ring_producer(sb, wg >> 1, sc[SC_EPOCH]);
    else if (warp == 1 && wg == 1) weight_producer(P, sb);
  }
  __syncwarp();
  asm volatile("barrier.cluster.arrive.release.aligned;\nbarrier.cluster.wait.acquire.aligned;" ::: "memory");
  if (tid == 0) { flag_add(C_DONE); TSTAMP(6); }
}

typedef CUresult (*EncodeFn)(CUtensorMap*, CUtensorMapDataType, cuuint32_t, void*, const cuuint64_t*, const cuuint64_t*, const cuuint32_t*,
                             const cuuint32_t*, CUtensorMapInterleave, CUtensorMapSwizzle, CUtensorMapL2promotion, CUtensorMapFloatOOBfill);

void make_map(EncodeFn enc, CUtensorMap* m, const void* ptr, int rows, int cols, int box_rows) {
  cuuint64_t dims[2] = {(cuuint64_t)cols, (cuuint64_t)rows}, strides[1] = {(cuuint64_t)cols * 2};
  cuuint32_t box[2] = {64, (cuuint32_t)box_rows}, es[2] = {1, 1};
  enc(m, CU_TENSOR_MAP_DATA_TYPE_BFLOAT16, 2, (void*)ptr, dims, strides, box, es, CU_TENSOR_MAP_INTERLEAVE_NONE,
      CU_TENSOR_MAP_SWIZZLE_128B, CU_TENSOR_MAP_L2_PROMOTION_L2_128B, CU_TENSOR_MAP_FLOAT_OOB_FILL_NONE);
}

}

extern "C" void kernel_launch(void* const* d_in, const int* in_sizes, int n_in, void* d_out, int out_size) {
  (void)in_sizes; (void)n_in; (void)out_size;
  static EncodeFn enc = nullptr;
  if (!enc) {
    cudaDriverEntryPointQueryResult qr;
    void* fn = nullptr;
    cudaGetDriverEntryPoint("cuTensorMapEncodeTiled", &fn, cudaEnableDefault, &qr);
    enc = (EncodeFn)fn;
    cudaFuncSetAttribute(fused_block_kernel, cudaFuncAttributeMaxDynamicSharedMemorySize, SMEM_BYTES);
  }
  Params P;
  const __nv_bfloat16* x = (const __nv_bfloat16*)d_in[0];
  make_map(enc, &P.tx, x, S_, D_, 128);
  make_map(enc, &P.twq, d_in[1], D_, D_, 64);
  make_map(enc, &P.two, d_in[4], D_, D_, 64);
  make_map(enc, &P.tw1, d_in[6], D_, F_, 64);
  make_map(enc, &P.tw2, d_in[7], F_, D_, 64);
  P.x = x; P.wk = (const __nv_bfloat16*)d_in[2]; P.wv = (const __nv_bfloat16*)d_in[3];
  P.wo = (const __nv_bfloat16*)d_in[4]; P.w1 = (const __nv_bfloat16*)d_in[6]; P.w2 = (const __nv_bfloat16*)d_in[7];
  P.out = (__nv_bfloat16*)d_out;
  P.c1 = 0xBF00BF00u; P.c2 = 0x00030003u; P.c3 = 0x9F809F80u;
  fused_block_kernel<<<NCTA, 512, SMEM_BYTES>>>(P);
}
```

```cpp
#include <cuda_runtime.h>
#include <cuda_bf16.h>
#include <cuda_fp16.h>
#include <cuda.h>
#include <stdint.h>

#define THR 2
#define DUTY 13
#define THR1 3
#define AWAIT 0
#define PACE 1
namespace {

constexpr int S_ = 2048, D_ = 512, F_ = 1376;
constexpr int NMAIN = 128, NAUX = 4, NCTA = NMAIN + NAUX;
constexpr float LN_EPS = 1e-5f;
constexpr float QK_SCALE_LOG2 = 0.25f * 1.4426950408889634f;

constexpr int KV_ROWS = 138, R_KP = 80, R_ST = 112, R_MX = 120, R_CS = 122;
__device__ __align__(1024) uint8_t g_kv[KV_ROWS * 2048];
constexpr int G_O = 0, G_H = 131072, G_HH = 262144, G_ST = G_HH + 344 * 1024, G_STRIDE = G_ST + 8192;
__device__ __align__(1024) uint8_t g_act[16 * G_STRIDE];
__device__ __align__(16) float g_cs1[F_ + 32];
__device__ __align__(1024) uint8_t g_w1t[8 * 176 * 1024];
constexpr int CNT_STRIDE = 32;
enum { C_KV = 0, C_AUX = 1, C_DONE = 2, C_O = 4, C_OB = C_O + 16, C_H = C_OB + 16, C_HH = C_H + 32, C_ST = C_HH + 32, C_NUM = C_ST + 32 };
__device__ unsigned int g_cnt[C_NUM * CNT_STRIDE];
#define TSTAMP(i) do {} while (0)
#define LSTAMP(c, i) do {} while (0)

constexpr int KB = 1024;
constexpr int CHB = 20 * KB;
constexpr int OFF_Q = 160 * KB;
constexpr int OFF_X = 0;
constexpr int OFF_WQ = 128 * KB;
constexpr int OFF_WKV = 192 * KB;
constexpr int OFF_WO = 56 * KB;
constexpr int OFF_RING = 176 * KB;
constexpr int OFF_MISC = 224 * KB;
constexpr int OFF_KVS = OFF_MISC;
constexpr int OFF_CS = OFF_KVS;
constexpr int OFF_ST2 = OFF_KVS + 768;
constexpr int OFF_FL = OFF_KVS + 1792;
constexpr int OFF_BAR = OFF_KVS + 2208;
constexpr int OFF_SC = OFF_BAR + 640;
constexpr int OFF_CSQ = OFF_WKV, OFF_ST1 = OFF_WKV + 256;
constexpr int SMEM_BYTES = OFF_MISC + 3072;
enum { B_XQ = 0  , B_WKV = 8, B_KV0 = 9, B_KV1 = 10, B_WO = 11, B_W1F = 12  , B_W2F = 20  , B_RF = 31  ,
       B_RED = 43  , B_TOK = 45  , B_RE = 50  , B_ADONE = 56, B_LAND = 57, B_W1E = 59  , B_SH = 67  ,
       B_SA = 69  , B_FB = 71  , B_ST2 = 73  , B_QS = 75, B_PDONE = 76, B_X01 = 77, B_XALL = 78, B_OWN = 58, B_F2 = 79, B_NUM = 80, B_OX = B_TOK, B_SW = B_TOK + 1   };
enum { SC_EPOCH = 0, SC_QMAX = 1, SC_KMAX = 2, SC_VMAX = 3, SC_FREE = 4   };
constexpr uint64_t W1_SLOT = 0x54327610u;
constexpr uint64_t W2_A0 = 0x3da2029062ce23ull, W2_A1 = 0x41cc0ad27ad244ull;
constexpr uint64_t W2_DEP = 0x99886544321ull;

__device__ __forceinline__ uint32_t s2u(const void* p) { return (uint32_t)__cvta_generic_to_shared(p); }
__device__ __forceinline__ void mbar_init(uint32_t b, int c) { asm volatile("mbarrier.init.shared::cta.b64 [%0], %1;" ::"r"(b), "r"(c) : "memory"); }
__device__ __forceinline__ void mbar_expect(uint32_t b, uint32_t n) { asm volatile("mbarrier.arrive.expect_tx.shared::cta.b64 _, [%0], %1;" ::"r"(b), "r"(n) : "memory"); }
__device__ __forceinline__ void mbar_arrive(uint32_t b) { asm volatile("mbarrier.arrive.shared::cta.b64 _, [%0];" ::"r"(b) : "memory"); }
__device__ __forceinline__ void mbar_wait(uint32_t b, uint32_t ph) {
  asm volatile("{\n.reg .pred p;\n.reg .u32 n;\nmov.u32 n, 0;\n"
               "W%=:\nmbarrier.try_wait.parity.shared::cta.b64 p, [%0], %1;\n@p bra D%=;\n"
               "add.u32 n, n, 1;\nsetp.lt.u32 p, n, 400000;\n@p bra W%=;\nD%=:\n}" ::"r"(b), "r"(ph) : "memory");
}
__device__ __forceinline__ void bulk_g2s(uint32_t dst, const void* src, uint32_t n, uint32_t bar) {
  asm volatile("cp.async.bulk.shared::cluster.global.mbarrier::complete_tx::bytes [%0], [%1], %2, [%3];" ::"r"(dst), "l"(src), "r"(n), "r"(bar) : "memory");
}
__device__ __forceinline__ void tma2d(uint32_t dst, const CUtensorMap* m, int c0, int c1, uint32_t bar) {
  asm volatile("cp.async.bulk.tensor.2d.shared::cluster.global.mbarrier::complete_tx::bytes [%0], [%1, {%3, %4}], [%2];"
               ::"r"(dst), "l"(m), "r"(bar), "r"(c0), "r"(c1) : "memory");
}
__device__ __forceinline__ void l2_prefetch(const void* p, uint32_t n) { asm volatile("cp.async.bulk.prefetch.L2.global [%0], %1;" ::"l"(p), "r"(n) : "memory"); }
__device__ __forceinline__ void fence_async_smem() { asm volatile("fence.proxy.async.shared::cta;" ::: "memory"); }
__device__ __forceinline__ void fence_async_all() { asm volatile("fence.proxy.async.global;" ::: "memory"); }
__device__ __forceinline__ void bar_sync(int id, int n) { asm volatile("bar.sync %0, %1;" ::"r"(id), "r"(n) : "memory"); }
__device__ __forceinline__ void flag_add(int c) { asm volatile("red.release.gpu.global.add.u32 [%0], 1;" ::"l"(&g_cnt[c * CNT_STRIDE]) : "memory"); }
__device__ __forceinline__ void flag_wait(int c, unsigned int target, int word = 0) {
  unsigned int v; int n = 0;
  do { asm volatile("ld.relaxed.gpu.global.u32 %0, [%1];" : "=r"(v) : "l"(&g_cnt[c * CNT_STRIDE + word]) : "memory");
     } while ((int)(v - target) < 0 && ++n < 400000);
  asm volatile("fence.acquire.gpu;" ::: "memory");
  fence_async_all();
}
__device__ __forceinline__ void mbar_wait2(uint32_t b0, uint32_t ph0, uint32_t b1) {
  asm volatile("{\n.reg .pred p, q;\n.reg .u32 n;\nmov.u32 n, 0;\n"
               "W%=:\nmbarrier.try_wait.parity.shared::cta.b64 p, [%0], %1;\nmbarrier.try_wait.parity.shared::cta.b64 q, [%2], 0;\n"
               "and.pred p, p, q;\n@p bra D%=;\n"
               "add.u32 n, n, 1;\nsetp.lt.u32 p, n, 400000;\n@p bra W%=;\nD%=:\n}" ::"r"(b0), "r"(ph0), "r"(b1) : "memory");
}
__device__ __forceinline__ bool elect_one() {
  uint32_t p;
  asm volatile("{\n.reg .pred P;\nelect.sync _|P, 0xffffffff;\nselp.u32 %0, 1, 0, P;\n}" : "=r"(p));
  return p != 0;
}
__device__ __forceinline__ int fresh_tid() { int t; asm volatile("mov.u32 %0, %%tid.x;" : "=r"(t)); return t; }
__device__ __forceinline__ int fresh_cta() { int t; asm volatile("mov.u32 %0, %%ctaid.x;" : "=r"(t)); return t; }
__device__ __forceinline__ uint32_t lds32(uint32_t a) { uint32_t v; asm volatile("ld.shared.u32 %0, [%1];" : "=r"(v) : "r"(a) : "memory"); return v; }
__device__ __forceinline__ void ldsm4t(uint32_t (&r)[4], uint32_t a) {
  asm volatile("ldmatrix.sync.aligned.m8n8.x4.trans.shared.b16 {%0,%1,%2,%3}, [%4];" : "=r"(r[0]), "=r"(r[1]), "=r"(r[2]), "=r"(r[3]) : "r"(a) : "memory");
}
__device__ __forceinline__ void store_finish(int flag, int word, uint32_t drained_bar) {
  asm volatile("cp.async.bulk.commit_group;" ::: "memory");
  if (drained_bar) { asm volatile("cp.async.bulk.wait_group.read 0;" ::: "memory"); mbar_arrive(drained_bar); }
  asm volatile("cp.async.bulk.wait_group 0;" ::: "memory");
  asm volatile("red.relaxed.gpu.global.add.u32 [%0], 1;" ::"l"(&g_cnt[flag * CNT_STRIDE + word]) : "memory");
}
__device__ __forceinline__ void bulk_s2g(void* dst, uint32_t src, uint32_t n) {
  asm volatile("cp.async.bulk.global.shared::cta.bulk_group [%0], [%1], %2;" ::"l"(dst), "r"(src), "r"(n) : "memory");
}
__device__ __forceinline__ void sts32(uint32_t a, uint32_t v) { asm volatile("st.shared.u32 [%0], %1;" ::"r"(a), "r"(v) : "memory"); }
__device__ __forceinline__ void stsm4(uint32_t a, uint32_t r0, uint32_t r1, uint32_t r2, uint32_t r3) {
  asm volatile("stmatrix.sync.aligned.m8n8.x4.shared.b16 [%0], {%1,%2,%3,%4};" ::"r"(a), "r"(r0), "r"(r1), "r"(r2), "r"(r3) : "memory");
}
__device__ __forceinline__ uint32_t stsm_off(int tid) { return (tid & 16) * 64 + (tid & 96) * 8 + (tid & 15) * 16; }
template <int N> __device__ __forceinline__ void undef(float (&d)[N]) {
#pragma unroll
  for (int i = 0; i < N; i++) asm volatile("" : "=f"(d[i]));
}
__device__ __forceinline__ void wg_fence() { asm volatile("wgmma.fence.sync.aligned;" ::: "memory"); }
__device__ __forceinline__ void wg_commit() { asm volatile("wgmma.commit_group.sync.aligned;" ::: "memory"); }
template <int N> __device__ __forceinline__ void wg_wait() { asm volatile("wgmma.wait_group.sync.aligned %0;" ::"n"(N) : "memory"); }
__device__ __forceinline__ uint64_t mkdesc(uint32_t addr, uint32_t lbo, uint32_t sbo, uint32_t swz = 0) {
  return (uint64_t)((addr & 0x3FFFF) >> 4) | ((uint64_t)(lbo >> 4) << 16) | ((uint64_t)(sbo >> 4) << 32) | ((uint64_t)swz << 62);
}
template <int N> __device__ __forceinline__ void pin(float (&d)[N]) {
#pragma unroll
  for (int i = 0; i < N; i++) asm volatile("" : "+f"(d[i])::"memory");
}
template <int N> __device__ __forceinline__ void pin(uint32_t (&d)[N]) {
#pragma unroll
  for (int i = 0; i < N; i++) asm volatile("" : "+r"(d[i])::"memory");
}
__device__ __forceinline__ uint32_t pack_bf16(float lo, float hi) { uint32_t r; asm("cvt.rn.bf16x2.f32 %0, %1, %2;" : "=r"(r) : "f"(hi), "f"(lo)); return r; }
__device__ __forceinline__ uint32_t pack_f16(float lo, float hi) { uint32_t r; asm("cvt.rn.f16x2.f32 %0, %1, %2;" : "=r"(r) : "f"(hi), "f"(lo)); return r; }
__device__ __forceinline__ float bf_lo(uint32_t u) { return __uint_as_float(u << 16); }
__device__ __forceinline__ float bf_hi(uint32_t u) { return __uint_as_float(u & 0xFFFF0000u); }
__device__ __forceinline__ float ex2(float x) { float r; asm("ex2.approx.ftz.f32 %0, %1;" : "=f"(r) : "f"(x)); return r; }
__device__ __forceinline__ void mma16816(float (&d)[4], uint32_t a0, uint32_t a1, uint32_t a2, uint32_t a3, uint32_t b0, uint32_t b1) {
  asm volatile("mma.sync.aligned.m16n8k16.row.col.f32.bf16.bf16.f32 {%0,%1,%2,%3},{%4,%5,%6,%7},{%8,%9},{%0,%1,%2,%3};"
               : "+f"(d[0]), "+f"(d[1]), "+f"(d[2]), "+f"(d[3]) : "r"(a0), "r"(a1), "r"(a2), "r"(a3), "r"(b0), "r"(b1));
}
__device__ __forceinline__ void mma16816h(float (&d)[4], uint32_t a0, uint32_t a1, uint32_t a2, uint32_t a3, uint32_t b0, uint32_t b1) {
  asm("mma.sync.aligned.m16n8k16.row.col.f32.f16.f16.f32 {%0,%1,%2,%3},{%4,%5,%6,%7},{%8,%9},{%10,%10,%10,%10};"
      : "=f"(d[0]), "=f"(d[1]), "=f"(d[2]), "=f"(d[3]) : "r"(a0), "r"(a1), "r"(a2), "r"(a3), "r"(b0), "r"(b1), "f"(0.f));
}
__device__ __forceinline__ void wgmma_n64_bt(float (&d)[32], uint64_t da, uint64_t db, int sd) {
  asm volatile("{.reg .pred p; setp.ne.b32 p, %34, 0;\n"
  "wgmma.mma_async.sync.aligned.m64n64k16.f32.bf16.bf16 {%0, %1, %2, %3, %4, %5, %6, %7, %8, %9, %10, %11, %12, %13, %14, %15, %16, %17, %18, %19, %20, %21, %22, %23, %24, %25, %26, %27, %28, %29, %30, %31}, %32, %33, p, 1, 1, 0, 1;}\n"
  : "+f"(d[0]), "+f"(d[1]), "+f"(d[2]), "+f"(d[3]), "+f"(d[4]), "+f"(d[5]), "+f"(d[6]), "+f"(d[7]), "+f"(d[8]), "+f"(d[9]), "+f"(d[10]), "+f"(d[11]), "+f"(d[12]), "+f"(d[13]), "+f"(d[14]), "+f"(d[15]), "+f"(d[16]), "+f"(d[17]), "+f"(d[18]), "+f"(d[19]), "+f"(d[20]), "+f"(d[21]), "+f"(d[22]), "+f"(d[23]), "+f"(d[24]), "+f"(d[25]), "+f"(d[26]), "+f"(d[27]), "+f"(d[28]), "+f"(d[29]), "+f"(d[30]), "+f"(d[31]) : "l"(da), "l"(db), "r"(sd));
}
__device__ __forceinline__ void wgmma_n128_bt(float (&d)[64], uint64_t da, uint64_t db, int sd) {
  asm volatile("{.reg .pred p; setp.ne.b32 p, %66, 0;\n"
  "wgmma.mma_async.sync.aligned.m64n128k16.f32.bf16.bf16 {%0, %1, %2, %3, %4, %5, %6, %7, %8, %9, %10, %11, %12, %13, %14, %15, %16, %17, %18, %19, %20, %21, %22, %23, %24, %25, %26, %27, %28, %29, %30, %31, %32, %33, %34, %35, %36, %37, %38, %39, %40, %41, %42, %43, %44, %45, %46, %47, %48, %49, %50, %51, %52, %53, %54, %55, %56, %57, %58, %59, %60, %61, %62, %63}, %64, %65, p, 1, 1, 0, 1;}\n"
  : "+f"(d[0]), "+f"(d[1]), "+f"(d[2]), "+f"(d[3]), "+f"(d[4]), "+f"(d[5]), "+f"(d[6]), "+f"(d[7]), "+f"(d[8]), "+f"(d[9]), "+f"(d[10]), "+f"(d[11]), "+f"(d[12]), "+f"(d[13]), "+f"(d[14]), "+f"(d[15]), "+f"(d[16]), "+f"(d[17]), "+f"(d[18]), "+f"(d[19]), "+f"(d[20]), "+f"(d[21]), "+f"(d[22]), "+f"(d[23]), "+f"(d[24]), "+f"(d[25]), "+f"(d[26]), "+f"(d[27]), "+f"(d[28]), "+f"(d[29]), "+f"(d[30]), "+f"(d[31]), "+f"(d[32]), "+f"(d[33]), "+f"(d[34]), "+f"(d[35]), "+f"(d[36]), "+f"(d[37]), "+f"(d[38]), "+f"(d[39]), "+f"(d[40]), "+f"(d[41]), "+f"(d[42]), "+f"(d[43]), "+f"(d[44]), "+f"(d[45]), "+f"(d[46]), "+f"(d[47]), "+f"(d[48]), "+f"(d[49]), "+f"(d[50]), "+f"(d[51]), "+f"(d[52]), "+f"(d[53]), "+f"(d[54]), "+f"(d[55]), "+f"(d[56]), "+f"(d[57]), "+f"(d[58]), "+f"(d[59]), "+f"(d[60]), "+f"(d[61]), "+f"(d[62]), "+f"(d[63]) : "l"(da), "l"(db), "r"(sd));
}
__device__ __forceinline__ void wgmma_n176_bt(float (&d)[88], uint64_t da, uint64_t db, int sd) {
  asm volatile("{.reg .pred p; setp.ne.b32 p, %90, 0;\n"
  "wgmma.mma_async.sync.aligned.m64n176k16.f32.bf16.bf16 {%0, %1, %2, %3, %4, %5, %6, %7, %8, %9, %10, %11, %12, %13, %14, %15, %16, %17, %18, %19, %20, %21, %22, %23, %24, %25, %26, %27, %28, %29, %30, %31, %32, %33, %34, %35, %36, %37, %38, %39, %40, %41, %42, %43, %44, %45, %46, %47, %48, %49, %50, %51, %52, %53, %54, %55, %56, %57, %58, %59, %60, %61, %62, %63, %64, %65, %66, %67, %68, %69, %70, %71, %72, %73, %74, %75, %76, %77, %78, %79, %80, %81, %82, %83, %84, %85, %86, %87}, %88, %89, p, 1, 1, 0, 1;}\n"
  : "+f"(d[0]), "+f"(d[1]), "+f"(d[2]), "+f"(d[3]), "+f"(d[4]), "+f"(d[5]), "+f"(d[6]), "+f"(d[7]), "+f"(d[8]), "+f"(d[9]), "+f"(d[10]), "+f"(d[11]), "+f"(d[12]), "+f"(d[13]), "+f"(d[14]), "+f"(d[15]), "+f"(d[16]), "+f"(d[17]), "+f"(d[18]), "+f"(d[19]), "+f"(d[20]), "+f"(d[21]), "+f"(d[22]), "+f"(d[23]), "+f"(d[24]), "+f"(d[25]), "+f"(d[26]), "+f"(d[27]), "+f"(d[28]), "+f"(d[29]), "+f"(d[30]), "+f"(d[31]), "+f"(d[32]), "+f"(d[33]), "+f"(d[34]), "+f"(d[35]), "+f"(d[36]), "+f"(d[37]), "+f"(d[38]), "+f"(d[39]), "+f"(d[40]), "+f"(d[41]), "+f"(d[42]), "+f"(d[43]), "+f"(d[44]), "+f"(d[45]), "+f"(d[46]), "+f"(d[47]), "+f"(d[48]), "+f"(d[49]), "+f"(d[50]), "+f"(d[51]), "+f"(d[52]), "+f"(d[53]), "+f"(d[54]), "+f"(d[55]), "+f"(d[56]), "+f"(d[57]), "+f"(d[58]), "+f"(d[59]), "+f"(d[60]), "+f"(d[61]), "+f"(d[62]), "+f"(d[63]), "+f"(d[64]), "+f"(d[65]), "+f"(d[66]), "+f"(d[67]), "+f"(d[68]), "+f"(d[69]), "+f"(d[70]), "+f"(d[71]), "+f"(d[72]), "+f"(d[73]), "+f"(d[74]), "+f"(d[75]), "+f"(d[76]), "+f"(d[77]), "+f"(d[78]), "+f"(d[79]), "+f"(d[80]), "+f"(d[81]), "+f"(d[82]), "+f"(d[83]), "+f"(d[84]), "+f"(d[85]), "+f"(d[86]), "+f"(d[87]) : "l"(da), "l"(db), "r"(sd));
}
__device__ __forceinline__ void wgmma_qk_f16(float (&d)[32], uint64_t da, uint64_t db, int sd) {
  asm volatile("{.reg .pred p; setp.ne.b32 p, %34, 0;\n"
  "wgmma.mma_async.sync.aligned.m64n64k16.f32.f16.f16 {%0, %1, %2, %3, %4, %5, %6, %7, %8, %9, %10, %11, %12, %13, %14, %15, %16, %17, %18, %19, %20, %21, %22, %23, %24, %25, %26, %27, %28, %29, %30, %31}, %32, %33, p, 1, 1, 0, 0;}\n"
  : "+f"(d[0]), "+f"(d[1]), "+f"(d[2]), "+f"(d[3]), "+f"(d[4]), "+f"(d[5]), "+f"(d[6]), "+f"(d[7]), "+f"(d[8]), "+f"(d[9]), "+f"(d[10]), "+f"(d[11]), "+f"(d[12]), "+f"(d[13]), "+f"(d[14]), "+f"(d[15]), "+f"(d[16]), "+f"(d[17]), "+f"(d[18]), "+f"(d[19]), "+f"(d[20]), "+f"(d[21]), "+f"(d[22]), "+f"(d[23]), "+f"(d[24]), "+f"(d[25]), "+f"(d[26]), "+f"(d[27]), "+f"(d[28]), "+f"(d[29]), "+f"(d[30]), "+f"(d[31]) : "l"(da), "l"(db), "r"(sd));
}
__device__ __forceinline__ void wgmma_qk_bf16(float (&d)[32], uint64_t da, uint64_t db, int sd) {
  asm volatile("{.reg .pred p; setp.ne.b32 p, %34, 0;\n"
  "wgmma.mma_async.sync.aligned.m64n64k16.f32.bf16.bf16 {%0, %1, %2, %3, %4, %5, %6, %7, %8, %9, %10, %11, %12, %13, %14, %15, %16, %17, %18, %19, %20, %21, %22, %23, %24, %25, %26, %27, %28, %29, %30, %31}, %32, %33, p, 1, 1, 0, 0;}\n"
  : "+f"(d[0]), "+f"(d[1]), "+f"(d[2]), "+f"(d[3]), "+f"(d[4]), "+f"(d[5]), "+f"(d[6]), "+f"(d[7]), "+f"(d[8]), "+f"(d[9]), "+f"(d[10]), "+f"(d[11]), "+f"(d[12]), "+f"(d[13]), "+f"(d[14]), "+f"(d[15]), "+f"(d[16]), "+f"(d[17]), "+f"(d[18]), "+f"(d[19]), "+f"(d[20]), "+f"(d[21]), "+f"(d[22]), "+f"(d[23]), "+f"(d[24]), "+f"(d[25]), "+f"(d[26]), "+f"(d[27]), "+f"(d[28]), "+f"(d[29]), "+f"(d[30]), "+f"(d[31]) : "l"(da), "l"(db), "r"(sd));
}
__device__ __forceinline__ void wgmma_pv(float (&d)[12], uint32_t a0, uint32_t a1, uint32_t a2, uint32_t a3, uint64_t db) {
  asm volatile("wgmma.mma_async.sync.aligned.m64n24k16.f32.bf16.bf16 {%0, %1, %2, %3, %4, %5, %6, %7, %8, %9, %10, %11}, {%12, %13, %14, %15}, %16, 1, 1, 1, 1;\n"
  : "+f"(d[0]), "+f"(d[1]), "+f"(d[2]), "+f"(d[3]), "+f"(d[4]), "+f"(d[5]), "+f"(d[6]), "+f"(d[7]), "+f"(d[8]), "+f"(d[9]), "+f"(d[10]), "+f"(d[11]) : "r"(a0), "r"(a1), "r"(a2), "r"(a3), "l"(db));
}

#define PAT "LLMMIILLMILLIIMM"
__host__ __device__ constexpr char ptype(int i) { return PAT[i]; }
constexpr float INIT_L = 256.0f + 127.0f - 77.164f / 128.0f + 1.0f / 256.0f;
constexpr float INIT_I = 256.0f + 190.0f - 75.041f / 128.0f + 1.0f / 256.0f;
__host__ __device__ constexpr float initv(int i) { return ptype(i) == 'M' ? 0.0f : ptype(i) == 'L' ? INIT_L : INIT_I; }
__device__ __forceinline__ uint32_t exp_pair(char ty, float a, float b, uint32_t c1, uint32_t c2, uint32_t c3) {
  if (ty == 'M') return pack_bf16(ex2(a), ex2(b));
  uint32_t y = __byte_perm(__float_as_uint(a), __float_as_uint(b), 0x6521), m, e, r;
  if (ty == 'L') {
    asm("lop3.b32 %0, %1, 0x007F007F, %2, 0xEA;" : "=r"(m) : "r"(y), "r"(c1));
    asm("lop3.b32 %0, %1, 0x7F807F80, %2, 0xEA;" : "=r"(e) : "r"(y), "r"(c2));
  } else {
    asm("lop3.b32 %0, %1, 0x007F007F, %2, 0xEA;" : "=r"(m) : "r"(y), "r"(c3));
    e = y - m;
  }
  asm("fma.rn.bf16x2 %0, %1, %2, %3;" : "=r"(r) : "r"(y), "r"(m), "r"(e));
  return r;
}
template <int HF> __device__ __forceinline__ void exp_half(const float (&s)[32], uint32_t (&p)[8], uint32_t c1, uint32_t c2, uint32_t c3) {
#pragma unroll
  for (int i = HF * 8; i < HF * 8 + 8; i++) p[i - HF * 8] = exp_pair(ptype(i), s[2 * i], s[2 * i + 1], c1, c2, c3);
}

struct Params {
  CUtensorMap tx, twq, two, tw2, tkv;
  const __nv_bfloat16 *x, *wq, *wk, *wv, *wo, *w1, *w2;
  __nv_bfloat16* out;
  uint32_t c1, c2, c3;
};

constexpr uint64_t RING_PAR = 0x8d333fc0000ull;
__device__ __forceinline__ int own_chunk(int j) { return (0x8630 >> (4 * (j >> 1))) & 15; }
__device__ __forceinline__ int k2_chunk(int j, int p) { const int a = own_chunk(j); return p < 2 ? a + p : p - 2 < a ? p - 2 : p; }
__device__ __forceinline__ int f_start(int j) { int n4 = j >> 1; return 688 * (j & 1) + (n4 == 3 ? 512 : 176 * n4); }

__device__ __forceinline__ void load_w1(uint32_t sb, int j, int k) {
  bulk_g2s(sb + (uint32_t)((W1_SLOT >> (4 * k)) & 7) * 22 * KB, g_w1t + (j * 8 + k) * 22 * KB, 22 * KB, sb + OFF_BAR + 8 * (B_W1F + k));
}

__device__ __forceinline__ void region_freed(const Params& P, uint32_t sb, int it, bool duty) {
  const uint32_t bars = sb + OFF_BAR;
  uint32_t old = 0;
  if (elect_one()) {
    if (duty) {
      const int g = fresh_cta() >> 3;
      if (it == 1) {
        asm volatile("cp.async.cg.shared.global [%0], [%1], 16;" ::"r"(sb + OFF_FL), "l"(&g_cnt[(C_O + g) * CNT_STRIDE]) : "memory");
        asm volatile("cp.async.cg.shared.global [%0], [%1], 16;" ::"r"(sb + OFF_FL + 16), "l"(&g_cnt[C_AUX * CNT_STRIDE]) : "memory");
      } else {
        asm volatile("cp.async.wait_all;" ::: "memory");
        mbar_wait(bars + 8 * B_F2, 0);
        const uint32_t e1 = lds32(sb + OFF_SC + 4 * SC_EPOCH) + 1;
        if ((int)((lds32(sb + OFF_FL) - e1 * 32) | (lds32(sb + OFF_FL + 16) - e1 * NAUX)) < 0) { flag_wait(C_O + g, e1 * 32); flag_wait(C_AUX, e1 * NAUX); }
        const int j = fresh_cta() & 7, n0 = min(j, 6) * 8 * KB;
        const uint8_t* src = g_act + (size_t)g * G_STRIDE + G_O;
        mbar_expect(bars + 8 * B_WO, 56 * KB);
        if (j) bulk_g2s(sb + OFF_RING, src, n0, bars + 8 * B_WO);
        if (j < 6) bulk_g2s(sb + OFF_RING + n0, src + n0 + 8 * KB, 48 * KB - n0, bars + 8 * B_WO);
        bulk_g2s(sb + 44 * KB, src + (j == 7 ? 48 : 56) * KB, 8 * KB, bars + 8 * B_WO);
      }
    }
    if (it == 1) mbar_arrive(bars + 8 * B_F2);
    else {
      asm volatile("atom.relaxed.cta.shared::cta.add.u32 %0, [%1], 1;" : "=r"(old) : "r"(sb + OFF_SC + 4 * SC_FREE) : "memory");
      if (old == 15) {
        const int j = fresh_cta() & 7;
        mbar_expect(bars + 8 * B_WO, 64 * KB);
        tma2d(sb + OFF_WO, &P.two, 64 * j, 0, bars + 8 * B_WO);
        tma2d(sb + OFF_WO + 32 * KB, &P.two, 64 * j, 256, bars + 8 * B_WO);
        mbar_expect(bars + 8 * B_W1F, 44 * KB);
        bulk_g2s(sb, g_w1t + j * 176 * KB, 44 * KB, bars + 8 * B_W1F);
      }
    }
  }
  __syncwarp();
}

__device__ __forceinline__ void publish_o(const float (&o)[12], uint32_t sb, int t, int wg, bool storer) {
  float i0, i1;
  asm("rcp.approx.ftz.f32 %0, %1;" : "=f"(i0) : "f"(o[8]));
  asm("rcp.approx.ftz.f32 %0, %1;" : "=f"(i1) : "f"(o[10]));
  const uint32_t stg = sb + OFF_Q + (t * 4 + wg) * 2048;
  stsm4(stg + stsm_off(fresh_tid()), pack_bf16(o[0] * i0, o[1] * i0), pack_bf16(o[2] * i1, o[3] * i1), pack_bf16(o[4] * i0, o[5] * i0), pack_bf16(o[6] * i1, o[7] * i1));
  const int cta = fresh_cta();
  uint8_t* dst = g_act + (size_t)(cta >> 3) * G_STRIDE + G_O + t * 65536 + (8 * (cta & 7) + 2 * wg) * 1024;
  fence_async_smem();
  if (storer) {
    bar_sync(2 + wg, 128);
    if (elect_one()) {
      bulk_s2g(dst, stg, 2048);
      if (t) TSTAMP(32 + wg);
    }
    __syncwarp();
  } else {
    asm volatile("bar.arrive %0, 128;" ::"r"(2 + wg) : "memory");
  }
}
__device__ __forceinline__ void finish_o(uint32_t sb, int t, bool storer) {
  if (storer) {
    if (elect_one()) {
      const int cta = fresh_cta();
      store_finish(C_O + 16 * t + (cta >> 3), t * (cta & 7), 0);
      if (t) mbar_arrive(sb + OFF_BAR + 8 * B_ADONE);
    }
    __syncwarp();
  }
}

__device__ __forceinline__ void attention_fast(const Params& P, uint32_t sb, int wg, bool duty, bool storer) {
  uint32_t c1 = P.c1, c2 = P.c2, c3 = P.c3;
  asm volatile("" : "+r"(c1), "+r"(c2), "+r"(c3));
#pragma unroll 1
  for (int t = 0; t < 2; t++) {
    float o[12], sA[32], sB[32];
    uint32_t pX[8], pY[8];
    const uint64_t dQ = mkdesc(sb + OFF_Q + (t * 4 + wg) * 2048, 1024, 128);
    uint64_t dK = mkdesc(sb, 4096, 128), dV = mkdesc(sb + 8192, 128, 4096);
#pragma unroll
    for (int i = 0; i < 12; i++) o[i] = 0.f;
#pragma unroll
    for (int i = 0; i < 16; i++) { sA[2 * i] = sA[2 * i + 1] = sB[2 * i] = sB[2 * i + 1] = initv(i); }
    pin(o); pin(sA); pin(sB);
    if (t == 0) mbar_wait(sb + OFF_BAR + 8 * B_KV0, 0);
    wg_fence();
    wgmma_qk_f16(sA, dQ, dK, 1);
    wgmma_qk_f16(sB, dQ, dK + 64, 1);
    wg_commit();
    if (t) finish_o(sb, 0, storer);
    wg_wait<0>();
#pragma unroll 1
    for (int it = 0; it < 4; it++) {
      pin(sA); pin(sB);
#pragma unroll
      for (int j = 0; j < 8; j++) {
        float(&s)[32] = (j & 1) ? sB : sA;
        const int voff = (j >> 2) * (CHB / 16) + (j & 3) * 64, koff = ((j + 2) >> 2) * (CHB / 16) + ((j + 2) & 3) * 64;
        if (j > 0) wg_wait<1>();
        pin(s); pin(pX);
        exp_half<0>(s, pX, c1, c2, c3);
        pin(pX);
        wg_fence();
        wgmma_pv(o, pX[0], pX[1], pX[2], pX[3], dV + voff);
        wgmma_pv(o, pX[4], pX[5], pX[6], pX[7], dV + voff + 16);
        wg_commit();
        if (j > 0) wg_wait<1>();
        pin(pY);
        exp_half<1>(s, pY, c1, c2, c3);
        pin(pY);
        wg_fence();
        wgmma_pv(o, pY[0], pY[1], pY[2], pY[3], dV + voff + 32);
        wgmma_pv(o, pY[4], pY[5], pY[6], pY[7], dV + voff + 48);
        wgmma_qk_f16(s, dQ, dK + koff, 1);
        wg_commit();
      }
      dK += 2 * (CHB / 16); dV += 2 * (CHB / 16);
      wg_wait<0>();
      if (t == 0) { if (it == 0) mbar_wait(sb + OFF_BAR + 8 * B_KV1, 0); }
      else if (it == 1 || it == 2) region_freed(P, sb, it, duty);
    }
    pin(o); pin(pX); pin(pY);
    publish_o(o, sb, t, wg, storer);
  }
}

__device__ __forceinline__ void attention_safe(const Params& P, uint32_t sb, int wg, bool duty, bool storer) {
#pragma unroll 1
  for (int t = 0; t < 2; t++) {
    float o[12], s[32], m0 = -INFINITY, m1 = -INFINITY;
    uint32_t p[16];
    const uint64_t dQ = mkdesc(sb + OFF_Q + (t * 4 + wg) * 2048, 1024, 128);
#pragma unroll
    for (int i = 0; i < 12; i++) o[i] = 0.f;
#pragma unroll
    for (int i = 0; i < 32; i++) s[i] = 0.f;
#pragma unroll 1
    for (int j = 0; j < 32; j++) {
      const uint32_t base = sb + (j >> 2) * CHB + (j & 3) * 1024;
      pin(s);
      wg_fence();
      wgmma_qk_bf16(s, dQ, mkdesc(base, 4096, 128), 0);
      wg_commit();
      wg_wait<0>();
      pin(s);
      float n0 = m0, n1 = m1;
#pragma unroll
      for (int i = 0; i < 16; i++) {
        const uint32_t r = pack_bf16(s[2 * i], s[2 * i + 1]);
        s[2 * i] = bf_lo(r); s[2 * i + 1] = bf_hi(r);
        if (i & 1) n1 = fmaxf(n1, fmaxf(s[2 * i], s[2 * i + 1])); else n0 = fmaxf(n0, fmaxf(s[2 * i], s[2 * i + 1]));
      }
      n0 = fmaxf(n0, __shfl_xor_sync(~0u, n0, 1)); n0 = fmaxf(n0, __shfl_xor_sync(~0u, n0, 2));
      n1 = fmaxf(n1, __shfl_xor_sync(~0u, n1, 1)); n1 = fmaxf(n1, __shfl_xor_sync(~0u, n1, 2));
      const float r0 = ex2((m0 - n0) * QK_SCALE_LOG2), r1 = ex2((m1 - n1) * QK_SCALE_LOG2);
      m0 = n0; m1 = n1;
#pragma unroll
      for (int i = 0; i < 12; i++) o[i] *= (i & 2) ? r1 : r0;
#pragma unroll
      for (int i = 0; i < 16; i++) {
        const float mm = (i & 1) ? m1 : m0;
        p[i] = pack_bf16(ex2((s[2 * i] - mm) * QK_SCALE_LOG2), ex2((s[2 * i + 1] - mm) * QK_SCALE_LOG2));
      }
      pin(o); pin(p);
      wg_fence();
      const uint64_t dV = mkdesc(base + 8192, 128, 4096);
#pragma unroll
      for (int k = 0; k < 4; k++) wgmma_pv(o, p[4 * k], p[4 * k + 1], p[4 * k + 2], p[4 * k + 3], dV + 16 * k);
      wg_commit();
      wg_wait<0>();
      pin(o); pin(p);
      if (t == 1 && (j == 15 || j == 23)) region_freed(P, sb, j >> 3, duty);
    }
    publish_o(o, sb, t, wg, storer);
    if (t == 0) finish_o(sb, 0, storer);
  }
}

__device__ __forceinline__ void aux_cta(const Params& P, uint8_t* smem) {
  const int a = blockIdx.x - NMAIN, tid = threadIdx.x, warp = tid >> 5, lane = tid & 31;
  const uint32_t sb = s2u(smem), bars = sb + OFF_BAR;
  constexpr int PITCH = 43 * 16 + 16;
  if (tid < 2) mbar_init(bars + 8 * tid, 256);
  __nanosleep(1000);
  fence_async_smem();
  __syncthreads();
  if (tid < 256) {
    mbar_expect(bars, 688);
    bulk_g2s(sb + tid * PITCH, P.w1 + (size_t)tid * F_ + a * 344, 688, bars);
  } else if (tid < 320) {
    l2_prefetch((const uint8_t*)P.w1 + 256 * 2752 + (size_t)(a * 64 + tid - 256) * 2752, 2752);
    l2_prefetch((const uint8_t*)P.wo + (size_t)(a * 64 + tid - 256) * 2048, 2048);
    l2_prefetch((const uint8_t*)P.w2 + (size_t)(a * 64 + tid - 256) * 5504, 5504);
  }
  if (tid == 0) TSTAMP(1);
  float acc[3][8];
#pragma unroll
  for (int q = 0; q < 3; q++)
#pragma unroll
    for (int i = 0; i < 8; i++) acc[q][i] = 0.f;
#pragma unroll 1
  for (int h = 0; h < 2; h++) {
    mbar_wait(bars + 8 * h, 0);
#pragma unroll
    for (int q = 0; q < 3; q++) {
      const int blk = warp + 16 * q;
      if (blk < 43) {
        const int hb = (a & 1) * 43 + blk, n4 = min(hb / 22, 3);
        const int d0 = ((2 * n4 + (a >> 1)) * 176 + hb - (n4 == 3 ? 64 : 22 * n4)) * KB;
        const int d1 = (hb == 64 || hb == 65) ? ((6 + (a >> 1)) * 176 + hb - 64) * KB : -1;
#pragma unroll
        for (int u = 0; u < 8; u++) {
          const int r = u * 32 + lane;
          const uint4 w = *(const uint4*)(smem + r * PITCH + blk * 16);
          uint8_t* dst = g_w1t + (h * 4 + (u >> 1)) * 22 * KB + (r & 63) * 16;
          *(uint4*)(dst + d0) = w;
          if (d1 >= 0) *(uint4*)(dst + d1) = w;
          acc[q][0] += bf_lo(w.x); acc[q][1] += bf_hi(w.x); acc[q][2] += bf_lo(w.y); acc[q][3] += bf_hi(w.y);
          acc[q][4] += bf_lo(w.z); acc[q][5] += bf_hi(w.z); acc[q][6] += bf_lo(w.w); acc[q][7] += bf_hi(w.w);
        }
      }
    }
    __syncthreads();
    if (h == 0 && tid < 256) {
      mbar_expect(bars + 8, 688);
      bulk_g2s(sb + tid * PITCH, P.w1 + (size_t)(256 + tid) * F_ + a * 344, 688, bars + 8);
    }
  }
  if (tid == 0) TSTAMP(2);
#pragma unroll
  for (int q = 0; q < 3; q++) {
#pragma unroll
    for (int i = 0; i < 8; i++)
#pragma unroll
      for (int o = 1; o < 32; o <<= 1) acc[q][i] += __shfl_xor_sync(~0u, acc[q][i], o);
    if (warp + 16 * q < 43 && lane == 0) {
      *(float4*)(g_cs1 + a * 344 + (warp + 16 * q) * 8) = make_float4(acc[q][0], acc[q][1], acc[q][2], acc[q][3]);
      *(float4*)(g_cs1 + a * 344 + (warp + 16 * q) * 8 + 4) = make_float4(acc[q][4], acc[q][5], acc[q][6], acc[q][7]);
    }
  }
  __syncthreads();
  if (tid == 0) { flag_add(C_AUX); flag_add(C_DONE); TSTAMP(0); }
}

__device__ __forceinline__ void kv_path(uint8_t* smem, uint32_t sb, const uint4 (&xr)[4]) {
  const int t = threadIdx.x - 256, w = t >> 5, lane = t & 31, g8 = lane >> 2, c = lane & 3;
  uint32_t xa[16] = {xr[0].x, xr[0].y, xr[0].z, xr[0].w, xr[2].x, xr[2].y, xr[2].z, xr[2].w,
                     xr[1].x, xr[1].y, xr[1].z, xr[1].w, xr[3].x, xr[3].y, xr[3].z, xr[3].w};
  if (c & 1) {
#pragma unroll
    for (int i = 0; i < 16; i += 2) { const uint32_t tmp = xa[i]; xa[i] = xa[i + 1]; xa[i + 1] = tmp; }
  }
  float s0 = 0, q0 = 0, s1 = 0, q1 = 0;
#pragma unroll
  for (int i = 0; i < 8; i++) {
    float a = bf_lo(xa[i]), b = bf_hi(xa[i]); s0 += a + b; q0 = fmaf(a, a, fmaf(b, b, q0));
    a = bf_lo(xa[8 + i]); b = bf_hi(xa[8 + i]); s1 += a + b; q1 = fmaf(a, a, fmaf(b, b, q1));
  }
  s0 += __shfl_xor_sync(~0u, s0, 1); q0 += __shfl_xor_sync(~0u, q0, 1); s1 += __shfl_xor_sync(~0u, s1, 1); q1 += __shfl_xor_sync(~0u, q1, 1);
  s0 += __shfl_xor_sync(~0u, s0, 2); q0 += __shfl_xor_sync(~0u, q0, 2); s1 += __shfl_xor_sync(~0u, s1, 2); q1 += __shfl_xor_sync(~0u, q1, 2);
  float d[4][4], e[4][4];
#pragma unroll
  for (int i = 0; i < 4; i++)
#pragma unroll
    for (int k = 0; k < 4; k++) { d[i][k] = 0.f; e[i][k] = 0.f; }
  const uint32_t one = 0x3F803F80u;
  const uint32_t la = sb + OFF_WKV + (64 * w + 8 * ((lane & 7) >> 1) + 2 * (((lane >> 3) ^ (lane >> 1)) & 1) + (lane & 1)) * 32 + (lane >> 4) * 16;
  mbar_wait(sb + OFF_BAR + 8 * B_WKV, 0);
  if (t == 0) TSTAMP(23);
#pragma unroll
  for (int ks = 0; ks < 4; ks++) {
    uint32_t bk[4], bv[4];
    ldsm4t(bk, la + (32 * (ks >> 1) + 4 * (ks & 1)) * 32);
    ldsm4t(bv, la + (32 * (ks >> 1) + 4 * (ks & 1)) * 32 + 16 * KB);
    const uint32_t a0 = xa[2 * ks], a1 = xa[8 + 2 * ks], a2 = xa[2 * ks + 1], a3 = xa[9 + 2 * ks];
    mma16816(d[0], a0, a1, a2, a3, bk[0], bk[1]); mma16816(d[1], a0, a1, a2, a3, bk[2], bk[3]);
    mma16816(d[2], a0, a1, a2, a3, bv[0], bv[1]); mma16816(d[3], a0, a1, a2, a3, bv[2], bv[3]);
    mma16816(e[0], one, one, one, one, bk[0], bk[1]); mma16816(e[1], one, one, one, one, bk[2], bk[3]);
    mma16816(e[2], one, one, one, one, bv[0], bv[1]); mma16816(e[3], one, one, one, one, bv[2], bv[3]);
  }
  __syncwarp();
  float* pw = (float*)(smem + OFF_WKV + w * 2048) + g8 * 18 + 2 * c;
#pragma unroll
  for (int i = 0; i < 4; i++) {
    *(float2*)(pw + (i >> 1) * 4096 + (i & 1) * 8) = make_float2(d[i][0], d[i][1]);
    *(float2*)(pw + (i >> 1) * 4096 + (i & 1) * 8 + 144) = make_float2(d[i][2], d[i][3]);
    if (g8 == 0) *(float2*)(pw + (i >> 1) * 4096 + (i & 1) * 8 + 288) = make_float2(e[i][0], e[i][1]);
  }
  if (c == 0) { *(float2*)(pw + 16) = make_float2(s0, q0); *(float2*)(pw + 160) = make_float2(s1, q1); }
  bar_sync(1, 256);
  const int row = lane & 15, cp = (2 * w + (lane >> 4)) & 7;
  float ax = 0, ay = 0, cx = 0, cy = 0, sm = 0, sq = 0;
  const float* pr = (const float*)(smem + OFF_WKV) + (w >> 2) * 4096 + 2 * cp;
#pragma unroll
  for (int i = 0; i < 8; i++) {
    const float2 a = *(const float2*)(pr + i * 512 + row * 18), cc = *(const float2*)(pr + i * 512 + 288);
    const float2 st = *(const float2*)((const float*)(smem + OFF_WKV) + i * 512 + row * 18 + 16);
    ax += a.x; ay += a.y; cx += cc.x; cy += cc.y; sm += st.x; sq += st.y;
  }
  const float mean = sm * (1.0f / D_), rstd = rsqrtf(fmaxf(sq * (1.0f / D_) - mean * mean, 0.f) + LN_EPS);
  uint32_t val = pack_bf16(rstd * (ax - mean * cx), rstd * (ay - mean * cy));
  uint8_t* stg = smem + OFF_KVS;
  float v0 = bf_lo(val), v1 = bf_hi(val);
  float nn = v0 * v0 + v1 * v1;
  nn += __shfl_xor_sync(~0u, nn, 16);
  const int sub = (cp >> 2) * 2 + (row & 1);
  if (w < 4) {
    *(uint32_t*)(stg + (R_KP + (row >> 1) * 4 + sub) * 16 + (cp & 3) * 4) = val;
    const float m = fmaxf(fabsf(v0), fabsf(v1));
    const float m3 = fmaxf(m, fmaxf(__shfl_up_sync(~0u, m, 1, 16), __shfl_down_sync(~0u, m, 1, 16)));
    const float magic = __uint_as_float((__float_as_uint(m3) & 0x7F800000u) + (14u << 23) + 0x00400000u);
    v0 = (v0 + magic) - magic; v1 = (v1 + magic) - magic;
    const float p0 = __shfl_up_sync(~0u, v0, 1, 16), p1 = __shfl_up_sync(~0u, v1, 1, 16);
    val = row ? pack_f16(v0 - p0, v1 - p1) : pack_f16(v0, v1);
  } else if (cp < 4) {
    *(uint32_t*)(stg + ((row >> 1) * 10 + 8 + (row & 1)) * 16 + cp * 4) = 0x3F803F80u;
  }
  *(uint32_t*)(stg + ((row >> 1) * 10 + (w >> 2) * 4 + sub) * 16 + (cp & 3) * 4) = val;
  const uint32_t nmax = __reduce_max_sync(~0u, __float_as_uint(nn));
  if (lane == 0) *(uint32_t*)(stg + R_MX * 16 + w * 4) = nmax;
  if (t < 16) *(float2*)(stg + R_ST * 16 + row * 8) = make_float2(mean, rstd);
  fence_async_smem();
  bar_sync(7, 320);
}

__device__ __forceinline__ void post_chain(const Params& P, uint8_t* smem, uint32_t sb, int hf) {
  const int tid = fresh_tid() & 127, warp = tid >> 5, lane = tid & 31, g8 = lane >> 2, c = lane & 3;
  const int cta = fresh_cta(), g = cta >> 3, j = cta & 7, gh = g * 2 + hf;
  const uint32_t bars = sb + OFF_BAR;
  const int row0 = g * 128 + hf * 64 + warp * 16 + g8;
  uint8_t* act = g_act + (size_t)g * G_STRIDE;
  const int frag = warp * 256 + lane * 4;
  const bool storer = __shfl_sync(~0u, warp, 0) == 3;
  const bool lead = elect_one();
  const uint32_t rf = bars + 8 * (B_RF + 6 * hf);
  const uint64_t dA = mkdesc(sb, 1024, 128);
  if (tid == 0) mbar_expect(bars + 8 * (B_RED + hf), 16 * KB);
  {
    uint32_t xr[16];
    const uint32_t* xp = (const uint32_t*)(P.x + (size_t)row0 * D_ + 64 * j + 2 * c);
#pragma unroll
    for (int b = 0; b < 8; b++) { xr[2 * b] = __ldg(xp + 4 * b); xr[2 * b + 1] = __ldg(xp + 8 * 256 + 4 * b); }
    float acc[32];
    undef(acc);
    const uint32_t stg = sb + (hf ? 120 * KB : OFF_RING);
    mbar_wait2(bars + 8 * (hf || AWAIT ? B_ADONE : B_WO), 0, bars + 8 * B_WO);
    if (tid == 0 && hf == 0) TSTAMP(29);
    const uint64_t dw = mkdesc(sb + OFF_WO, 8192, 1024, 1);
    wg_fence();
#pragma unroll
    for (int s = 0; s < 4; s++) wgmma_n64_bt(acc, dA + ((OFF_Q + hf * 8 * KB) >> 4) + 128 * s, dw + 512 * j + 128 * s, s);
    wg_commit();
#pragma unroll
    for (int k = 0; k < 7; k++) {
      const int u = hf ? k : (k + 6) % 7;
      const uint64_t da = dA + (u == 6 ? 44 * 64 : (hf ? 120 * 64 : OFF_RING >> 4) + 512 * u), db = dw + 512 * (u < j ? u : u + 1);
      if (hf) mbar_wait(k < 6 ? rf + 8 * k : bars + 8 * B_OX, 0);
      else if (PACE) { wg_wait<0>(); if (k == 1 && lead) mbar_arrive(bars + 8 * B_OWN); }
      else if (k == 2) { wg_wait<1>(); if (lead) mbar_arrive(bars + 8 * B_OWN); }
      wg_fence();
#pragma unroll
      for (int s = 0; s < 4; s++) wgmma_n64_bt(acc, da + 128 * s, db + 128 * s, 1);
      wg_commit();
    }
    wg_wait<0>();
    pin(acc);
    if (lane < 7 && (lane == 6 || !hf)) mbar_arrive(bars + 8 * (lane < 6 ? B_RE + lane : B_PDONE));
    if (tid == 0) TSTAMP(30 + hf);
#pragma unroll
    for (int b = 0; b < 8; b++) {
      xr[2 * b] = pack_bf16(acc[4 * b] + bf_lo(xr[2 * b]), acc[4 * b + 1] + bf_hi(xr[2 * b]));
      xr[2 * b + 1] = pack_bf16(acc[4 * b + 2] + bf_lo(xr[2 * b + 1]), acc[4 * b + 3] + bf_hi(xr[2 * b + 1]));
      if (b & 1) stsm4(stg + stsm_off(tid) + (b - 1) * 1024, xr[2 * b - 2], xr[2 * b - 1], xr[2 * b], xr[2 * b + 1]);
    }
    fence_async_smem();
    bar_sync(6 + hf, 128);
    if (storer && lead) {
      bulk_s2g(act + G_H + (hf * 8 + j) * 8192, stg, 8192);
      store_finish(C_H + gh, j, bars + 8 * (B_SA + hf));
      TSTAMP(40 + hf);
    }
    __syncwarp();
    pin(xr);
    float s0 = 0, q0 = 0, s1 = 0, q1 = 0;
#pragma unroll
    for (int b = 0; b < 8; b++) {
      float u = bf_lo(xr[2 * b]), v = bf_hi(xr[2 * b]); s0 += u + v; q0 = fmaf(u, u, fmaf(v, v, q0));
      u = bf_lo(xr[2 * b + 1]); v = bf_hi(xr[2 * b + 1]); s1 += u + v; q1 = fmaf(u, u, fmaf(v, v, q1));
    }
    s0 += __shfl_xor_sync(~0u, s0, 1); q0 += __shfl_xor_sync(~0u, q0, 1); s1 += __shfl_xor_sync(~0u, s1, 1); q1 += __shfl_xor_sync(~0u, q1, 1);
    s0 += __shfl_xor_sync(~0u, s0, 2); q0 += __shfl_xor_sync(~0u, q0, 2); s1 += __shfl_xor_sync(~0u, s1, 2); q1 += __shfl_xor_sync(~0u, q1, 2);
    *(float*)(act + G_ST + (hf * 8 + j) * 512 + tid * 4) = c == 0 ? s0 : c == 1 ? q0 : c == 2 ? s1 : q1;
    __syncwarp();
    if (lead) flag_add(C_ST + gh);
    __syncwarp();
  }
  if (tid == 0) TSTAMP(8 + hf * 8);
  asm volatile("setmaxnreg.inc.sync.aligned.u32 208;");
  {
    float acc[88];
    undef(acc);
#define RSLOT(r0, r1) ((r0) % 6 + hf * ((r1) % 6 - (r0) % 6))
#define RPAR(r0, r1) ((int)(RING_PAR >> (r0) & 1) + hf * ((int)(RING_PAR >> (r1) & 1) - (int)(RING_PAR >> (r0) & 1)))
    const uint64_t dR = dA + (OFF_RING >> 4), dW = mkdesc(sb, 128, 1024);
    mbar_wait2(rf + 8 * RSLOT(12, 20), RPAR(12, 20), bars + 8 * B_W1F);
    if (tid == 0) TSTAMP(13 + hf * 8);
    wg_fence();
#pragma unroll
    for (int k = 0; k < 8; k++) {
      const uint64_t da = dR + 512 * RSLOT(12 + k, 20 + k), db = dW + ((W1_SLOT >> (4 * k)) & 7) * 1408;
      wgmma_n176_bt(acc, da, db, k);
      wgmma_n176_bt(acc, da + 128, db + 16, 1);
      wg_commit();
      if (k > 0) {
        wg_wait<1>();
        if (lane < 2) mbar_arrive(bars + 8 * (lane ? B_W1E + k - 1 : B_RE + RSLOT(11 + k, 19 + k)));
      }
      wgmma_n176_bt(acc, da + 256, db + 32, 1);
      wg_commit();
      if (k < 7) mbar_wait2(rf + 8 * RSLOT(13 + k, 21 + k), RPAR(13 + k, 21 + k), bars + 8 * (B_W1F + k + 1));
      wg_fence();
      wgmma_n176_bt(acc, da + 384, db + 48, 1);
      wg_commit();
    }
    mbar_wait(bars + 8 * (B_ST2 + hf), 0);
    const float4 ln = *(const float4*)(smem + OFF_ST2 + hf * 512 + (tid >> 2) * 16);
    const float hr0 = ln.x, m0 = ln.y, hr1 = ln.z, m1 = ln.w;
    wg_wait<0>();
    pin(acc);
    if (lane < 2) mbar_arrive(bars + 8 * (lane ? B_W1E + 7 : B_RE + RSLOT(19, 27)));
    if (tid == 0) TSTAMP(9 + hf * 8);
    const float2* cs = (const float2*)(smem + OFF_CS) + c;
    const uint32_t stg = sb + (hf ? 110 * KB : 0);
    uint32_t hp[20];
    float2 cn[4] = {cs[0], cs[4], cs[8], cs[12]};
#pragma unroll
    for (int b = 0; b < 22; b++) {
      const float2 cc = cn[b & 3];
      if (b + 4 < 22) cn[b & 3] = cs[4 * (b + 4)];
      float v[4] = {fmaf(acc[4 * b], hr0, m0 * cc.x), fmaf(acc[4 * b + 1], hr0, m0 * cc.y),
                    fmaf(acc[4 * b + 2], hr1, m1 * cc.x), fmaf(acc[4 * b + 3], hr1, m1 * cc.y)};
#pragma unroll
      for (int i = 0; i < 4; i++) {
        float th; asm("tanh.approx.f32 %0, %1;" : "=f"(th) : "f"(v[i]));
        v[i] = fmaf(v[i], th, v[i]);
      }
      const int q = b < 10 ? 2 * b : 2 * (b & 1);
      hp[q] = pack_bf16(v[0], v[1]);
      hp[q + 1] = pack_bf16(v[2], v[3]);
      if (b == 9) {
        pin(hp);
        mbar_wait(bars + 8 * (B_W1E + 7 * hf), 0);
#pragma unroll
        for (int s = 0; s < 5; s++) stsm4(stg + stsm_off(tid) + s * 2048, hp[4 * s], hp[4 * s + 1], hp[4 * s + 2], hp[4 * s + 3]);
      } else if (b > 9 && (b & 1)) {
        stsm4(stg + stsm_off(tid) + (b >> 1) * 2048, hp[0], hp[1], hp[2], hp[3]);
      }
    }
    if (tid == 0) TSTAMP(56 + hf);
    fence_async_smem();
    bar_sync(6 + hf, 128);
    if (storer && lead) {
      bulk_s2g(act + G_HH + (hf * 172 + (f_start(j) >> 3)) * 1024, stg, 22 * KB);
      store_finish(C_HH + gh, j, bars + 8 * (B_SH + hf));
      TSTAMP(42 + hf);
    }
    __syncwarp();
  }
  if (tid == 0) TSTAMP(10 + hf * 8);
  {
    float acc[64];
    undef(acc);
    uint32_t hr[16];
    const uint8_t* himg = act + G_H + (hf * 8 + j) * 8192 + frag;
#pragma unroll
    for (int b = 0; b < 8; b++) { hr[2 * b] = __ldcg((const uint32_t*)(himg + b * 1024)); hr[2 * b + 1] = __ldcg((const uint32_t*)(himg + b * 1024 + 128)); }
    const int kh = j & 1;
    uint32_t peer;
    asm volatile("mapa.shared::cluster.u32 %0, %1, %2;" : "=r"(peer) : "r"(sb), "r"(kh ^ 1));
    const uint64_t dR = dA + (OFF_RING >> 4), dW = mkdesc(sb, 0, 1024, 1);
    {
      const uint64_t da = dA + (hf ? 110 * 64 : 0) + (4 * own_chunk(j) - (f_start(j) - 688 * kh) / 16) * 128;
      mbar_wait2(bars + 8 * B_W2F, 0, bars + 8 * (B_W2F + 1));
      wg_fence();
#pragma unroll
      for (int s = 0; s < 8; s++) wgmma_n128_bt(acc, da + 128 * s, dW + ((s < 4 ? 3 : 17) * 512 + (1 << 25) + 128 * (s & 3)), s);
      wg_commit();
      wg_wait<0>();
      if (lead) {
        mbar_arrive(bars + 8 * (B_SW + hf));
        asm volatile("mbarrier.arrive.relaxed.cluster.shared::cluster.b64 _, [%0];" ::"r"(peer + OFF_BAR + 8 * B_LAND) : "memory");
      }
    }
    mbar_wait2(rf + 8 * RSLOT(28, 37), RPAR(28, 37), bars + 8 * (B_W2F + 2));
    if (tid == 0) TSTAMP(14 + hf * 8);
    wg_fence();
#pragma unroll
    for (int i = 2; i < 11; i++) {
      const uint32_t a0 = (uint32_t)(W2_A0 >> (5 * i)) & 31, a1 = (uint32_t)(W2_A1 >> (5 * i)) & 31;
      const uint64_t da = dR + 512 * RSLOT(26 + i, 35 + i), db = dW + (a0 * 512 + ((a1 - a0) << 25));
      wgmma_n128_bt(acc, da, db, 1);
      wgmma_n128_bt(acc, da + 128, db + 128, 1);
      wg_commit();
      if (i > 2) {
        wg_wait<1>();
        if (lead) mbar_arrive(bars + 8 * (B_RE + RSLOT(25 + i, 34 + i)));
      }
      wgmma_n128_bt(acc, da + 256, db + 256, 1);
      wg_commit();
      if (i < 10) {
        mbar_wait2(rf + 8 * RSLOT(27 + i, 36 + i), RPAR(27 + i, 36 + i), bars + 8 * (B_W2F + i + 1));
        wg_fence();
        wgmma_n128_bt(acc, da + 384, db + 384, 1);
        wg_commit();
      }
    }
    wg_wait<0>();
    pin(acc);
    if (lead) mbar_arrive(bars + 8 * (B_RE + RSLOT(36, 45)));
    if (tid == 0) TSTAMP(11 + hf * 8);
    mbar_wait(bars + 8 * B_LAND, 0);
    const uint32_t land = (hf ? 136 : 24) * KB + tid * 16;
#pragma unroll
    for (int i = 0; i < 8; i++)
      asm volatile("st.async.shared::cluster.mbarrier::complete_tx::bytes.v4.f32 [%0], {%1,%2,%3,%4}, [%5];"
                   ::"r"(peer + land + i * 2048), "f"(acc[32 + 4 * i]), "f"(acc[33 + 4 * i]), "f"(acc[34 + 4 * i]), "f"(acc[35 + 4 * i]),
                     "r"(peer + OFF_BAR + 8 * (B_RED + hf)) : "memory");
    if (tid == 0) TSTAMP(58 + hf);
    mbar_wait(bars + 8 * (B_RED + hf), 0);
    if (tid == 0) TSTAMP(60 + hf);
    float4 r[8];
#pragma unroll
    for (int i = 0; i < 8; i++) r[i] = *(const float4*)(smem + land + i * 2048);
    uint32_t* op = (uint32_t*)(P.out + (size_t)row0 * D_ + 64 * j + 2 * c);
#pragma unroll
    for (int i = 0; i < 8; i++) {
      op[4 * i] = pack_bf16(acc[4 * i] + r[i].x + bf_lo(hr[2 * i]), acc[4 * i + 1] + r[i].y + bf_hi(hr[2 * i]));
      op[8 * 256 + 4 * i] = pack_bf16(acc[4 * i + 2] + r[i].z + bf_lo(hr[2 * i + 1]), acc[4 * i + 3] + r[i].w + bf_hi(hr[2 * i + 1]));
    }
    if (tid == 0) TSTAMP(12 + hf * 8);
  }
}

__device__ __forceinline__ void ring_producer(uint32_t sb, int slot) {
  const int cta = fresh_cta(), g = cta >> 3, j = cta & 7, lane = fresh_tid() & 31;
  const uint32_t bars = sb + OFF_BAR, e1 = lds32(sb + OFF_SC + 4 * SC_EPOCH) + 1;
  const uint8_t* act = g_act + (size_t)g * G_STRIDE;
#pragma unroll 1
  for (int r = 6 + slot; r < 46; r += 6) {
    int hf, off, line, word, own;
    uint32_t bytes = 8 * KB, target = e1;
    if (r < 12) { hf = 1; word = r - 6 + (r - 6 >= j); off = G_O + 65536 + word * 8 * KB; line = C_OB + g; own = B_ADONE; target = 4 * e1; }
    else if (r < 28) { hf = r >= 20; word = (r - 12) & 7; off = G_H + (r - 12) * 8 * KB; line = C_H + 2 * g + hf; own = B_SA + hf; }
    else {
      hf = r >= 37;
      const int i = k2_chunk(j, r - 26 - 9 * hf);
      word = 2 * min((4 * i + 3 * (lane & 1)) / 11, 3) + (j & 1);
      off = G_HH + (hf * 172 + (j & 1) * 86 + 8 * i) * KB; line = C_HH + 2 * g + hf; own = B_SH + hf;
      if (i == 10) bytes = 6 * KB;
    }
    const uint32_t fb = bars + 8 * (B_RF + 6 * hf + slot);
    mbar_wait(bars + 8 * own, 0);
    flag_wait(line, target, word);
    if (r >= 11) mbar_wait(bars + 8 * (r == 11 ? B_OWN : B_RE + slot), r < 12 ? 0 : (r / 6) & 1);
    if (elect_one()) {
      mbar_expect(fb, bytes);
      bulk_g2s(sb + (r < 12 ? 120 * KB : OFF_RING) + slot * 8 * KB, act + off, bytes, fb);
    }
  }
}

__device__ __forceinline__ void ln2_stats(uint8_t* smem, uint32_t sb) {
  const int g = fresh_cta() >> 3, lane = fresh_tid() & 31;
  const uint32_t bars = sb + OFF_BAR, epoch = lds32(sb + OFF_SC + 4 * SC_EPOCH);
  {
    const int u = (fresh_cta() & 7) == 7 ? 6 : 7;
    mbar_wait(bars + 8 * B_ADONE, 0);
    if (lane == 0) mbar_expect(bars + 8 * B_OX, 8 * KB);
    flag_wait(C_OB + g, (epoch + 1) * 4, u);
    mbar_wait(bars + 8 * B_OWN, 0);
    if (elect_one()) bulk_g2s(sb + 44 * KB, g_act + (size_t)g * G_STRIDE + G_O + 65536 + u * 8 * KB, 8 * KB, bars + 8 * B_OX);
  }
#pragma unroll 1
  for (int hf = 0; hf < 2; hf++) {
    mbar_wait(bars + 8 * (B_SA + hf), 0);
    flag_wait(C_ST + g * 2 + hf, (epoch + 1) * 32);
    const float4* sp = (const float4*)(g_act + (size_t)g * G_STRIDE + G_ST + hf * 4096) + lane;
    float4 a = __ldcg(sp);
#pragma unroll
    for (int i = 1; i < 8; i++) { const float4 v = __ldcg(sp + 32 * i); a.x += v.x; a.y += v.y; a.z += v.z; a.w += v.w; }
    const float mean0 = a.x * (1.0f / D_), hr0 = 0.5f * rsqrtf(fmaxf(a.y * (1.0f / D_) - mean0 * mean0, 0.f) + LN_EPS);
    const float mean1 = a.z * (1.0f / D_), hr1 = 0.5f * rsqrtf(fmaxf(a.w * (1.0f / D_) - mean1 * mean1, 0.f) + LN_EPS);
    *(float4*)(smem + OFF_ST2 + hf * 512 + lane * 16) = make_float4(hr0, -mean0 * hr0, hr1, -mean1 * hr1);
    __syncwarp();
    if (lane == 0) mbar_arrive(bars + 8 * (B_ST2 + hf));
  }
}

__device__ __forceinline__ void weight_producer(const Params& P, uint32_t sb) {
  const int j = fresh_cta() & 7;
  const uint32_t bars = sb + OFF_BAR;
  if (elect_one()) {
    mbar_arrive(bars + 8 * (B_W1F + 1));
    fence_async_all();
#pragma unroll 1
    for (int k = 2; k < 8; k++) {
      mbar_wait2(bars + 8 * (k == 7 ? B_SA + 1 : B_PDONE), 0, bars + 8 * (B_W1F + max(k - THR1, 0)));
      if (k == 2) TSTAMP(15);
      mbar_expect(bars + 8 * (B_W1F + k), k == 2 ? 22 * KB + 704 : 22 * KB);
      if (k == 2) bulk_g2s(sb + OFF_CS, g_cs1 + f_start(j), 704, bars + 8 * (B_W1F + 2));
      load_w1(sb, j, k);
    }
    const int n0 = j * 64, k0 = (j & 1) * 688;
#pragma unroll 1
    for (int i = 0; i < 11; i++) {
      mbar_wait2(bars + 8 * (B_W1E + (int)((W2_DEP >> (4 * i)) & 15)), 0, bars + 8 * (B_W2F + i - THR));
      if (i == 7 || i == 9) mbar_wait(bars + 8 * (B_SW + (i == 9)), 0);
      const int kc = k0 + 64 * k2_chunk(j, i);
      mbar_expect(bars + 8 * (B_W2F + i), 16 * KB);
      tma2d(sb + ((uint32_t)(W2_A0 >> (5 * i)) & 31) * 8 * KB, &P.tw2, n0, kc, bars + 8 * (B_W2F + i));
      tma2d(sb + ((uint32_t)(W2_A1 >> (5 * i)) & 31) * 8 * KB, &P.tw2, n0 ^ 64, kc, bars + 8 * (B_W2F + i));
    }
  }
}

__global__ void __cluster_dims__(2, 1, 1) __launch_bounds__(512, 1) fused_block_kernel(const __grid_constant__ Params P) {
  extern __shared__ __align__(1024) uint8_t smem[];
  if (blockIdx.x >= NMAIN) { aux_cta(P, smem); return; }
  const uint32_t sb = s2u(smem), bars = sb + OFF_BAR;
  bool fast;
  {
    const int tid = threadIdx.x, lane = tid & 31;
    const int wid = __shfl_sync(~0u, tid >> 5, 0), wg = wid >> 2;
    const int g = blockIdx.x >> 3, j = blockIdx.x & 7;
    uint32_t* sc = (uint32_t*)(smem + OFF_SC);
    float qacc[32];
    const uint32_t qdst = sb + OFF_Q + wg * 8192 + stsm_off(tid);
    if (wg < 2) {
      if (tid == 0) TSTAMP(0);
      if (wid == 1) {
        const bool el = elect_one();
        if (el) {
          mbar_init(bars + 8 * B_WKV, 1);
          mbar_expect(bars + 8 * B_WKV, 32 * KB);
          bulk_g2s(sb + OFF_WKV, P.wk, 16 * KB, bars + 8 * B_WKV);
          bulk_g2s(sb + OFF_WKV + 16 * KB, P.wv, 16 * KB, bars + 8 * B_WKV);
#pragma unroll
          for (int k = 0; k < 8; k++) mbar_init(bars + 8 * (B_XQ + k), 1);
        }
        __syncwarp();
        asm volatile("bar.arrive 0, 512;" ::: "memory");
        if (elect_one()) {
#pragma unroll 1
          for (int k = 0; k < 8; k++) {
            mbar_expect(bars + 8 * (B_XQ + k), 24 * KB);
            tma2d(sb + OFF_X + 16 * KB * k, &P.tx, 64 * k, 128 * g, bars + 8 * (B_XQ + k));
            tma2d(sb + OFF_WQ + 8 * KB * k, &P.twq, 64 * j, 64 * k, bars + 8 * (B_XQ + k));
          }
        }
      } else {
        if (wid >= 3 && elect_one()) asm volatile("prefetch.tensormap [%0];" ::"l"(&P.tx + (wid - 3)) : "memory");
        if (wid) bar_sync(0, 512);
        else {
          asm volatile("bar.arrive 0, 512;" ::: "memory");
          float cs[8];
#pragma unroll
          for (int i = 0; i < 8; i++) cs[i] = 0.f;
          const uint4* wp = (const uint4*)(P.wq + (32 * (blockIdx.x & 15) + (lane >> 3)) * D_ + 64 * (blockIdx.x >> 4)) + (lane & 7);
#pragma unroll
          for (int h = 0; h < 8; h++) {
            const uint4 v = __ldg(wp + h * 256);
            cs[0] += bf_lo(v.x); cs[1] += bf_hi(v.x); cs[2] += bf_lo(v.y); cs[3] += bf_hi(v.y);
            cs[4] += bf_lo(v.z); cs[5] += bf_hi(v.z); cs[6] += bf_lo(v.w); cs[7] += bf_hi(v.w);
          }
#pragma unroll
          for (int i = 0; i < 8; i++) { cs[i] += __shfl_xor_sync(~0u, cs[i], 8); cs[i] += __shfl_xor_sync(~0u, cs[i], 16); }
          if (lane < 8) {
            *(float4*)(smem + OFF_KVS + R_CS * 16 + lane * 32) = make_float4(cs[0], cs[1], cs[2], cs[3]);
            *(float4*)(smem + OFF_KVS + R_CS * 16 + lane * 32 + 16) = make_float4(cs[4], cs[5], cs[6], cs[7]);
          }
          fence_async_smem();
        }
        if (wid == 2 && elect_one()) {
#pragma unroll
          for (int i = B_KV0; i < B_NUM; i++)
            mbar_init(bars + 8 * i, i == B_WO ? 2 : i == B_SW || i == B_SW + 1 || i == B_OWN ? 4 : i < B_RE ? 1 : i < B_LAND ? 4 : i < B_SH ? 8 : i < B_QS ? 1 : i == B_QS ? 2 : i == B_F2 ? 16 : 8);
#pragma unroll
          for (int i = 1; i < 7; i++) sc[i] = 0;
          asm volatile("fence.mbarrier_init.release.cluster;" ::: "memory");
        }
        __syncwarp();
        if (wid == 0 || wid == 2) asm volatile("bar.arrive 7, 320;" ::: "memory");
      }
      undef(qacc);
      const bool lead = elect_one();
      bar_sync(6, 512);
#pragma unroll 1
      for (int k = 0; k < 8; k++) {
        mbar_wait(bars + 8 * (B_XQ + k), 0);
        const uint64_t da = mkdesc(sb + OFF_X + wg * 8 * KB, 16, 1024, 1) + 1024 * k, db = mkdesc(sb + OFF_WQ, 8192, 1024, 1) + 512 * k;
        wg_fence();
#pragma unroll
        for (int s = 0; s < 4; s++) wgmma_n64_bt(qacc, da + 2 * s, db + 128 * s, s ? 1 : k);
        wg_commit();
        wg_wait<1>();
        if (k == 4 && lead) mbar_arrive(bars + 8 * B_X01);
      }
      wg_wait<0>();
      pin(qacc);
      if (lead) mbar_arrive(bars + 8 * B_XALL);
      if (tid == 0) TSTAMP(1);
      mbar_wait(bars + 8 * B_QS, 0);
      mbar_wait(bars + 8 * B_XALL, 0);
      const float2* sp = (const float2*)(smem + OFF_ST1) + wid * 16 + (lane >> 2);
      const float2 st0 = sp[0], st1 = sp[8];
      const float2* cs = (const float2*)(smem + OFF_CSQ) + (lane & 3);
      const float r0 = st0.y * QK_SCALE_LOG2, r1 = st1.y * QK_SCALE_LOG2, m0 = -st0.x * r0, m1 = -st1.x * r1;
      uint32_t nmax = 0;
#pragma unroll
      for (int h = 0; h < 4; h++) {
        uint32_t qh[4];
#pragma unroll
        for (int b = 2 * h; b < 2 * h + 2; b++) {
          const float2 cc = cs[4 * b];
          qacc[4 * b] = fmaf(qacc[4 * b], r0, m0 * cc.x); qacc[4 * b + 1] = fmaf(qacc[4 * b + 1], r0, m0 * cc.y);
          qacc[4 * b + 2] = fmaf(qacc[4 * b + 2], r1, m1 * cc.x); qacc[4 * b + 3] = fmaf(qacc[4 * b + 3], r1, m1 * cc.y);
          qh[2 * (b & 1)] = pack_f16(qacc[4 * b], qacc[4 * b + 1]);
          qh[2 * (b & 1) + 1] = pack_f16(qacc[4 * b + 2], qacc[4 * b + 3]);
        }
        stsm4(qdst + h * 2048, qh[0], qh[1], qh[2], qh[3]);
        float u[4], v[4];
        mma16816h(u, qh[0], qh[1], qh[2], qh[3], qh[0], qh[2]);
        mma16816h(v, qh[0], qh[1], qh[2], qh[3], qh[1], qh[3]);
        nmax = max(max(nmax, __float_as_uint(fabsf(u[0]))), __float_as_uint(fabsf(u[1])));
        nmax = max(max(nmax, __float_as_uint(fabsf(v[2]))), __float_as_uint(fabsf(v[3])));
      }
      nmax = __reduce_max_sync(~0u, nmax);
      if (lane == 0) atomicMax(&sc[SC_QMAX], nmax);
    } else {
      uint4 xr[4];
      const __nv_bfloat16* xp = P.x + (size_t)(blockIdx.x * 16 + (lane >> 2)) * D_ + 64 * (wid - 8) + 8 * (lane & 3);
      xr[0] = __ldg((const uint4*)xp); xr[1] = __ldg((const uint4*)(xp + 8 * D_));
      xr[2] = __ldg((const uint4*)(xp + 32)); xr[3] = __ldg((const uint4*)(xp + 8 * D_ + 32));
      uint32_t done = 0;
      if (wid >= 14) done = *(volatile unsigned int*)&g_cnt[C_DONE * CNT_STRIDE];
      bar_sync(0, 512);
      kv_path(smem, sb, xr);
      asm volatile("bar.arrive 6, 512;" ::: "memory");
      if (wid == 8) {
        if (elect_one()) {
          TSTAMP(27);
          asm volatile("cp.async.bulk.tensor.2d.global.shared::cta.bulk_group [%0, {%2, %3}], [%1];"
                       ::"l"(&P.tkv), "r"(sb + OFF_KVS), "r"(8 * (int)blockIdx.x), "r"(0) : "memory");
          store_finish(C_KV, 0, 0);
          TSTAMP(2);
        }
      } else if (wid >= 12) {
        if (wid == 15) flag_wait(C_KV, (done / NCTA + 1) * NMAIN);
        bar_sync(5, 128);
        if (wid == 15) {
          if (elect_one()) {
            TSTAMP(3);
            mbar_wait(bars + 8 * B_X01, 0);
            mbar_expect(bars + 8 * B_KV0, 3 * CHB);
#pragma unroll 1
            for (int c = 0; c < 3; c++) bulk_g2s(sb + c * CHB, g_kv + c * CHB, CHB, bars + 8 * B_KV0);
            mbar_wait(bars + 8 * B_XALL, 0);
            mbar_wait(bars + 8 * B_QS, 0);
            mbar_expect(bars + 8 * B_KV1, 5 * CHB);
#pragma unroll 1
            for (int c = 3; c < 8; c++) bulk_g2s(sb + c * CHB, g_kv + c * CHB, CHB, bars + 8 * B_KV1);
          }
        } else if (wid == 14) {
          uint32_t km = 0, vm = 0;
#pragma unroll
          for (int i = 0; i < 4; i++) {
            const float4 a = __ldcg((const float4*)(g_kv + R_MX * 2048) + lane + 32 * i), b = __ldcg((const float4*)(g_kv + R_MX * 2048) + 128 + lane + 32 * i);
            km = max(km, __float_as_uint(a.x + a.y + a.z + a.w)); vm = max(vm, __float_as_uint(b.x + b.y + b.z + b.w));
          }
          km = __reduce_max_sync(~0u, km); vm = __reduce_max_sync(~0u, vm);
          if (lane == 0) { sc[SC_KMAX] = km; sc[SC_VMAX] = vm; sc[SC_EPOCH] = done / NCTA; }
        } else {
          if (wid == 13) {
            const float4* cp = (const float4*)(g_kv + (R_CS + (lane >> 1)) * 2048) + j * 16 + (lane & 1);
            float4 acc = __ldcg(cp);
#pragma unroll
            for (int i = 1; i < 8; i++) { const float4 v = __ldcg(cp + 2 * i); acc.x += v.x; acc.y += v.y; acc.z += v.z; acc.w += v.w; }
            acc.x += __shfl_xor_sync(~0u, acc.x, 1); acc.y += __shfl_xor_sync(~0u, acc.y, 1);
            acc.z += __shfl_xor_sync(~0u, acc.z, 1); acc.w += __shfl_xor_sync(~0u, acc.w, 1);
            if (lane & 1) *(float4*)(smem + OFF_CSQ + (lane >> 1) * 16) = acc;
          } else {
            const float4* sp = (const float4*)(g_kv + (R_ST + (lane >> 3)) * 2048) + g * 8 + (lane & 7);
            const float4 u = __ldcg(sp), v = __ldcg(sp + 512);
            *(float4*)(smem + OFF_ST1 + (lane & 7) * 128 + (lane >> 3) * 16) = u;
            *(float4*)(smem + OFF_ST1 + (lane & 7) * 128 + (lane >> 3) * 16 + 64) = v;
          }
          __syncwarp();
          if (lane == 0) mbar_arrive(bars + 8 * B_QS);
          if (tid == 416) TSTAMP(26);
        }
      }
      __syncwarp();
    }
    fence_async_smem();
    __syncthreads();
    const float q2 = __uint_as_float(sc[SC_QMAX]), k2 = __uint_as_float(sc[SC_KMAX]), v2 = __uint_as_float(sc[SC_VMAX]);
    fast = __all_sync(~0u, (q2 * k2 <= 56.f * 56.f) && (q2 <= 1048576.f) && (k2 <= 1048576.f) && (v2 <= 1e24f));
    if (tid == 0) TSTAMP(4);
    if (!fast) {
      mbar_wait(bars + 8 * B_KV0, 0);
      mbar_wait(bars + 8 * B_KV1, 0);
      if (wg < 2) {
#pragma unroll
        for (int h = 0; h < 4; h++) {
          constexpr float u = 1.0f / QK_SCALE_LOG2;
          stsm4(qdst + h * 2048, pack_bf16(qacc[8 * h] * u, qacc[8 * h + 1] * u), pack_bf16(qacc[8 * h + 2] * u, qacc[8 * h + 3] * u),
                pack_bf16(qacc[8 * h + 4] * u, qacc[8 * h + 5] * u), pack_bf16(qacc[8 * h + 6] * u, qacc[8 * h + 7] * u));
        }
      }
      for (int e = tid; e < 4096; e += 512) *(uint4*)(smem + (e >> 9) * CHB + (e & 511) * 16) = __ldcg((const uint4*)(g_kv + R_KP * 2048) + e);
      fence_async_smem();
      __syncthreads();
    }
  }
  {
    const int wq = __shfl_sync(~0u, fresh_tid() >> 5, 0), wg = wq >> 2;
    if (fast) attention_fast(P, sb, wg, wq == DUTY, (wq & 3) == 3);
    else attention_safe(P, sb, wg, wq == DUTY, (wq & 3) == 3);
    finish_o(sb, 1, (wq & 3) == 3);
  }
  const int wid = __shfl_sync(~0u, fresh_tid() >> 5, 0);
  if (fresh_tid() == 0) TSTAMP(5);
  if ((wid & 4) == 0) {
    post_chain(P, smem, sb, wid < 4);
    if (fresh_tid() == 0) { asm volatile("red.relaxed.gpu.global.add.u32 [%0], 1;" ::"l"(&g_cnt[C_DONE * CNT_STRIDE]) : "memory"); TSTAMP(6); }
  } else {
    asm volatile("setmaxnreg.dec.sync.aligned.u32 48;");
    if (wid == 15) weight_producer(P, sb);
    else if (wid == 7) ln2_stats(smem, sb);
    else ring_producer(sb, wid >= 12 ? wid - 12 : wid - 1);
  }
}

typedef CUresult (*EncodeFn)(CUtensorMap*, CUtensorMapDataType, cuuint32_t, void*, const cuuint64_t*, const cuuint64_t*, const cuuint32_t*,
                             const cuuint32_t*, CUtensorMapInterleave, CUtensorMapSwizzle, CUtensorMapL2promotion, CUtensorMapFloatOOBfill);

void make_map(EncodeFn enc, CUtensorMap* m, const void* ptr, int rows, int cols, int box_rows, int box_cols = 64) {
  cuuint64_t dims[2] = {(cuuint64_t)cols, (cuuint64_t)rows}, strides[1] = {(cuuint64_t)cols * 2};
  cuuint32_t box[2] = {(cuuint32_t)box_cols, (cuuint32_t)box_rows}, es[2] = {1, 1};
  enc(m, CU_TENSOR_MAP_DATA_TYPE_BFLOAT16, 2, (void*)ptr, dims, strides, box, es, CU_TENSOR_MAP_INTERLEAVE_NONE,
      box_cols == 64 ? CU_TENSOR_MAP_SWIZZLE_128B : CU_TENSOR_MAP_SWIZZLE_NONE, CU_TENSOR_MAP_L2_PROMOTION_L2_128B, CU_TENSOR_MAP_FLOAT_OOB_FILL_NONE);
}

}

extern "C" void kernel_launch(void* const* d_in, const int* in_sizes, int n_in, void* d_out, int out_size) {
  (void)in_sizes; (void)n_in; (void)out_size;
  static EncodeFn enc = nullptr;
  if (!enc) {
    cudaDriverEntryPointQueryResult qr;
    void* fn = nullptr;
    cudaGetDriverEntryPoint("cuTensorMapEncodeTiled", &fn, cudaEnableDefault, &qr);
    enc = (EncodeFn)fn;
    cudaFuncSetAttribute(fused_block_kernel, cudaFuncAttributeMaxDynamicSharedMemorySize, SMEM_BYTES);
  }
  Params P;
  const __nv_bfloat16* x = (const __nv_bfloat16*)d_in[0];
  make_map(enc, &P.tx, x, S_, D_, 128);
  make_map(enc, &P.twq, d_in[1], D_, D_, 64);
  make_map(enc, &P.two, d_in[4], D_, D_, 256);
  make_map(enc, &P.tw2, d_in[7], F_, D_, 64);
  void* kv = nullptr;
  cudaGetSymbolAddress(&kv, g_kv);
  make_map(enc, &P.tkv, kv, KV_ROWS, 1024, KV_ROWS, 8);
  P.x = x; P.wq = (const __nv_bfloat16*)d_in[1]; P.wk = (const __nv_bfloat16*)d_in[2]; P.wv = (const __nv_bfloat16*)d_in[3];
  P.wo = (const __nv_bfloat16*)d_in[4]; P.w1 = (const __nv_bfloat16*)d_in[6]; P.w2 = (const __nv_bfloat16*)d_in[7];
  P.out = (__nv_bfloat16*)d_out;
  P.c1 = 0xBF00BF00u; P.c2 = 0x00030003u; P.c3 = 0x9F809F80u;
  fused_block_kernel<<<NCTA, 512, SMEM_BYTES>>>(P);
}
```

```cpp
#include <cuda_runtime.h>
#include <cuda_bf16.h>
#include <cuda_fp16.h>
#include <cuda.h>
#include <stdint.h>

#define FORCE_REDO 0
namespace {

constexpr int S_ = 2048, D_ = 512, F_ = 1376;
constexpr int NMAIN = 128, NAUX = 4, NCTA = NMAIN + NAUX;
constexpr float LN_EPS = 1e-5f;
constexpr float QK_SCALE_LOG2 = 0.25f * 1.4426950408889634f;

constexpr int KV_ROWS = 138, R_KP = 80, R_ST = 112, R_MX = 120, R_CS = 122;
__device__ __align__(1024) uint8_t g_kv[KV_ROWS * 2048];
constexpr int G_O = 0, G_H = 131072, G_HH = 262144, G_ST = G_HH + 344 * 1024, G_STRIDE = G_ST + 8192;
__device__ __align__(1024) uint8_t g_act[16 * G_STRIDE];
__device__ __align__(16) float g_cs1[F_ + 32];
__device__ __align__(1024) uint8_t g_w1t[8 * 176 * 1024];
constexpr int CNT_STRIDE = 32;
enum { C_KV = 0, C_AUX = 1, C_DONE = 2, C_O = 4, C_OB = C_O + 16, C_H = C_OB + 16, C_HH = C_H + 32, C_NUM = C_HH + 32 };
__device__ unsigned int g_cnt[C_NUM * CNT_STRIDE];
#define TSTAMP(i) do {} while (0)
#define LSTAMP(c, i) do {} while (0)

constexpr int KB = 1024;
constexpr int CHB = 20 * KB;
constexpr int OFF_Q = 160 * KB;
constexpr int OFF_X = 0;
constexpr int OFF_WQ = 128 * KB;
constexpr int OFF_WKV = 192 * KB;
constexpr int OFF_WO = 56 * KB;
constexpr int OFF_RING = 176 * KB;
constexpr int OFF_FILL = 200 * KB;
constexpr int OFF_MISC = 224 * KB;
constexpr int OFF_KVS = OFF_MISC;
constexpr int OFF_CS = OFF_KVS;
constexpr int OFF_ST2 = OFF_KVS + 768;
constexpr int OFF_FL = OFF_KVS + 1792;
constexpr int OFF_BAR = OFF_KVS + 2208;
constexpr int OFF_SC = OFF_BAR + 656;
constexpr int OFF_CSQ = OFF_WKV, OFF_ST1 = OFF_WKV + 256;
constexpr int SMEM_BYTES = OFF_MISC + 3072;
enum { B_XQ = 0  , B_WKV = 8,
       B_KV0 = 9, B_KV1 = 10, B_W1F = 11  , B_W2F = 19  , B_RF = 30  , B_RED = 42  , B_OX = 44, B_ST2 = 45  ,
       B_WO = 47, B_QS = 48,
       B_RE = 49  , B_OWN = 55, B_SA = 56  , B_S1 = 58  , B_SH = 60  , B_SW = 62  ,
       B_W1E = 64  , B_LAND = 72, B_PDONE = 73, B_X01 = 74, B_XALL = 75,
       B_ADONE = 76, B_F2 = 77, B_OA = 78, B_NUM = 79 };
enum { SC_EPOCH = 0, SC_QMAX = 1, SC_KMAX = 2, SC_VMAX = 3, SC_FREE = 4   };
constexpr uint64_t W1_SLOT = 0x54327610u;
constexpr uint64_t W2_A0 = 0x3da2029062ce23ull, W2_A1 = 0x41cc0ad27ad244ull;
constexpr uint64_t W2_DEP = 0x11008766543ull;

__device__ __forceinline__ uint32_t s2u(const void* p) { return (uint32_t)__cvta_generic_to_shared(p); }
__device__ __forceinline__ void mbar_init(uint32_t b, int c) { asm volatile("mbarrier.init.shared::cta.b64 [%0], %1;" ::"r"(b), "r"(c) : "memory"); }
__device__ __forceinline__ void mbar_expect(uint32_t b, uint32_t n) { asm volatile("mbarrier.arrive.expect_tx.shared::cta.b64 _, [%0], %1;" ::"r"(b), "r"(n) : "memory"); }
__device__ __forceinline__ void mbar_arrive(uint32_t b) { asm volatile("mbarrier.arrive.shared::cta.b64 _, [%0];" ::"r"(b) : "memory"); }
__device__ __forceinline__ void mbar_wait(uint32_t b, uint32_t ph) {
  asm volatile("{\n.reg .pred p;\n.reg .u32 n;\nmov.u32 n, 0;\n"
               "W%=:\nmbarrier.try_wait.parity.shared::cta.b64 p, [%0], %1;\n@p bra D%=;\n"
               "add.u32 n, n, 1;\nsetp.lt.u32 p, n, 400000;\n@p bra W%=;\nD%=:\n}" ::"r"(b), "r"(ph) : "memory");
}
__device__ __forceinline__ void bulk_g2s(uint32_t dst, const void* src, uint32_t n, uint32_t bar) {
  asm volatile("cp.async.bulk.shared::cluster.global.mbarrier::complete_tx::bytes [%0], [%1], %2, [%3];" ::"r"(dst), "l"(src), "r"(n), "r"(bar) : "memory");
}
__device__ __forceinline__ void tma2d(uint32_t dst, const CUtensorMap* m, int c0, int c1, uint32_t bar) {
  asm volatile("cp.async.bulk.tensor.2d.shared::cluster.global.mbarrier::complete_tx::bytes [%0], [%1, {%3, %4}], [%2];"
               ::"r"(dst), "l"(m), "r"(bar), "r"(c0), "r"(c1) : "memory");
}
__device__ __forceinline__ void l2_prefetch(const void* p, uint32_t n) { asm volatile("cp.async.bulk.prefetch.L2.global [%0], %1;" ::"l"(p), "r"(n) : "memory"); }
__device__ __forceinline__ void fence_async_smem() { asm volatile("fence.proxy.async.shared::cta;" ::: "memory"); }
__device__ __forceinline__ void fence_async_all() { asm volatile("fence.proxy.async.global;" ::: "memory"); }
__device__ __forceinline__ void bar_sync(int id, int n) { asm volatile("bar.sync %0, %1;" ::"r"(id), "r"(n) : "memory"); }
__device__ __forceinline__ void flag_add(int c) { asm volatile("red.release.gpu.global.add.u32 [%0], 1;" ::"l"(&g_cnt[c * CNT_STRIDE]) : "memory"); }
__device__ __forceinline__ void flag_wait(int c, unsigned int target, int word = 0) {
  unsigned int v; int n = 0;
  do { asm volatile("ld.relaxed.gpu.global.u32 %0, [%1];" : "=r"(v) : "l"(&g_cnt[c * CNT_STRIDE + word]) : "memory");
     } while ((int)(v - target) < 0 && ++n < 400000);
  asm volatile("fence.acquire.gpu;" ::: "memory");
  fence_async_all();
}
__device__ __forceinline__ void mbar_wait2(uint32_t b0, uint32_t ph0, uint32_t b1) {
  asm volatile("{\n.reg .pred p, q;\n.reg .u32 n;\nmov.u32 n, 0;\n"
               "W%=:\nmbarrier.try_wait.parity.shared::cta.b64 p, [%0], %1;\nmbarrier.try_wait.parity.shared::cta.b64 q, [%2], 0;\n"
               "and.pred p, p, q;\n@p bra D%=;\n"
               "add.u32 n, n, 1;\nsetp.lt.u32 p, n, 400000;\n@p bra W%=;\nD%=:\n}" ::"r"(b0), "r"(ph0), "r"(b1) : "memory");
}
__device__ __forceinline__ bool elect_one() {
  uint32_t p;
  asm volatile("{\n.reg .pred P;\nelect.sync _|P, 0xffffffff;\nselp.u32 %0, 1, 0, P;\n}" : "=r"(p));
  return p != 0;
}
__device__ __forceinline__ int fresh_tid() { int t; asm volatile("mov.u32 %0, %%tid.x;" : "=r"(t)); return t; }
__device__ __forceinline__ int fresh_cta() { int t; asm volatile("mov.u32 %0, %%ctaid.x;" : "=r"(t)); return t; }
__device__ __forceinline__ uint32_t lds32(uint32_t a) { uint32_t v; asm volatile("ld.shared.u32 %0, [%1];" : "=r"(v) : "r"(a) : "memory"); return v; }
__device__ __forceinline__ void ldsm4t(uint32_t (&r)[4], uint32_t a) {
  asm volatile("ldmatrix.sync.aligned.m8n8.x4.trans.shared.b16 {%0,%1,%2,%3}, [%4];" : "=r"(r[0]), "=r"(r[1]), "=r"(r[2]), "=r"(r[3]) : "r"(a) : "memory");
}
__device__ __forceinline__ void hint_add(int flag, int word) {
  asm volatile("red.relaxed.gpu.global.add.u32 [%0], 1;" ::"l"(&g_cnt[flag * CNT_STRIDE + word]) : "memory");
}
__device__ __forceinline__ void stg32(void* p, uint32_t v) { asm volatile("st.global.u32 [%0], %1;" ::"l"(p), "r"(v) : "memory"); }
__device__ __forceinline__ void bulk_s2g(void* dst, uint32_t src, uint32_t n) {
  asm volatile("cp.async.bulk.global.shared::cta.bulk_group [%0], [%1], %2;" ::"l"(dst), "r"(src), "r"(n) : "memory");
}
__device__ __forceinline__ void stsm4(uint32_t a, uint32_t r0, uint32_t r1, uint32_t r2, uint32_t r3) {
  asm volatile("stmatrix.sync.aligned.m8n8.x4.shared.b16 [%0], {%1,%2,%3,%4};" ::"r"(a), "r"(r0), "r"(r1), "r"(r2), "r"(r3) : "memory");
}
__device__ __forceinline__ uint32_t stsm_off(int tid) { return (tid & 16) * 64 + (tid & 96) * 8 + (tid & 15) * 16; }
template <int N> __device__ __forceinline__ void undef(float (&d)[N]) {
#pragma unroll
  for (int i = 0; i < N; i++) asm volatile("" : "=f"(d[i]));
}
__device__ __forceinline__ void wg_fence() { asm volatile("wgmma.fence.sync.aligned;" ::: "memory"); }
__device__ __forceinline__ void wg_commit() { asm volatile("wgmma.commit_group.sync.aligned;" ::: "memory"); }
template <int N> __device__ __forceinline__ void wg_wait() { asm volatile("wgmma.wait_group.sync.aligned %0;" ::"n"(N) : "memory"); }
__device__ __forceinline__ uint64_t mkdesc(uint32_t addr, uint32_t lbo, uint32_t sbo, uint32_t swz = 0) {
  return (uint64_t)((addr & 0x3FFFF) >> 4) | ((uint64_t)(lbo >> 4) << 16) | ((uint64_t)(sbo >> 4) << 32) | ((uint64_t)swz << 62);
}
template <int N> __device__ __forceinline__ void pin(float (&d)[N]) {
#pragma unroll
  for (int i = 0; i < N; i++) asm volatile("" : "+f"(d[i])::"memory");
}
template <int N> __device__ __forceinline__ void pin(uint32_t (&d)[N]) {
#pragma unroll
  for (int i = 0; i < N; i++) asm volatile("" : "+r"(d[i])::"memory");
}
__device__ __forceinline__ uint32_t pack_bf16(float lo, float hi) { uint32_t r; asm("cvt.rn.bf16x2.f32 %0, %1, %2;" : "=r"(r) : "f"(hi), "f"(lo)); return r; }
__device__ __forceinline__ uint32_t pack_f16(float lo, float hi) { uint32_t r; asm("cvt.rn.f16x2.f32 %0, %1, %2;" : "=r"(r) : "f"(hi), "f"(lo)); return r; }
__device__ __forceinline__ float bf_lo(uint32_t u) { return __uint_as_float(u << 16); }
__device__ __forceinline__ float bf_hi(uint32_t u) { return __uint_as_float(u & 0xFFFF0000u); }
template <int NB> __device__ __forceinline__ void redo_gemm(float (&acc)[4 * NB], const uint8_t* img, int kn, const __nv_bfloat16* w, int ldw, int flip) {
  if (!FORCE_REDO && !__any_sync(~0u, isnan(acc[0] + acc[2]))) return;
#pragma unroll
  for (int i = 0; i < 4 * NB; i++) acc[i] = 0.f;
#pragma unroll 1
  for (int k = 0; k < kn; k++) {
    uint32_t a0, a1;
    int n = 0;
    do {
      asm volatile("ld.relaxed.gpu.global.u32 %0, [%1];" : "=r"(a0) : "l"(img + (k >> 3) * 1024 + (k & 6) * 2) : "memory");
      asm volatile("ld.relaxed.gpu.global.u32 %0, [%1];" : "=r"(a1) : "l"(img + (k >> 3) * 1024 + (k & 6) * 2 + 128) : "memory");
    } while (max(a0, a1) == 0xFFFFFFFFu && ++n < 10000);
    const float x0 = (k & 1) ? bf_hi(a0) : bf_lo(a0), x1 = (k & 1) ? bf_hi(a1) : bf_lo(a1);
#pragma unroll
    for (int b = 0; b < NB; b++) {
      const uint32_t v = __ldg((const uint32_t*)(w + (size_t)k * ldw + (b < 8 ? 8 * b : 8 * b + flip)));
      acc[4 * b] = fmaf(x0, bf_lo(v), acc[4 * b]); acc[4 * b + 1] = fmaf(x0, bf_hi(v), acc[4 * b + 1]);
      acc[4 * b + 2] = fmaf(x1, bf_lo(v), acc[4 * b + 2]); acc[4 * b + 3] = fmaf(x1, bf_hi(v), acc[4 * b + 3]);
    }
  }
}
__device__ __forceinline__ float ex2(float x) { float r; asm("ex2.approx.ftz.f32 %0, %1;" : "=f"(r) : "f"(x)); return r; }
__device__ __forceinline__ void mma16816(float (&d)[4], uint32_t a0, uint32_t a1, uint32_t a2, uint32_t a3, uint32_t b0, uint32_t b1) {
  asm volatile("mma.sync.aligned.m16n8k16.row.col.f32.bf16.bf16.f32 {%0,%1,%2,%3},{%4,%5,%6,%7},{%8,%9},{%0,%1,%2,%3};"
               : "+f"(d[0]), "+f"(d[1]), "+f"(d[2]), "+f"(d[3]) : "r"(a0), "r"(a1), "r"(a2), "r"(a3), "r"(b0), "r"(b1));
}
__device__ __forceinline__ void mma16816h(float (&d)[4], uint32_t a0, uint32_t a1, uint32_t a2, uint32_t a3, uint32_t b0, uint32_t b1) {
  asm("mma.sync.aligned.m16n8k16.row.col.f32.f16.f16.f32 {%0,%1,%2,%3},{%4,%5,%6,%7},{%8,%9},{%10,%10,%10,%10};"
      : "=f"(d[0]), "=f"(d[1]), "=f"(d[2]), "=f"(d[3]) : "r"(a0), "r"(a1), "r"(a2), "r"(a3), "r"(b0), "r"(b1), "f"(0.f));
}
__device__ __forceinline__ void wgmma_n64_bt(float (&d)[32], uint64_t da, uint64_t db, int sd) {
  asm volatile("{.reg .pred p; setp.ne.b32 p, %34, 0;\n"
  "wgmma.mma_async.sync.aligned.m64n64k16.f32.bf16.bf16 {%0, %1, %2, %3, %4, %5, %6, %7, %8, %9, %10, %11, %12, %13, %14, %15, %16, %17, %18, %19, %20, %21, %22, %23, %24, %25, %26, %27, %28, %29, %30, %31}, %32, %33, p, 1, 1, 0, 1;}\n"
  : "+f"(d[0]), "+f"(d[1]), "+f"(d[2]), "+f"(d[3]), "+f"(d[4]), "+f"(d[5]), "+f"(d[6]), "+f"(d[7]), "+f"(d[8]), "+f"(d[9]), "+f"(d[10]), "+f"(d[11]), "+f"(d[12]), "+f"(d[13]), "+f"(d[14]), "+f"(d[15]), "+f"(d[16]), "+f"(d[17]), "+f"(d[18]), "+f"(d[19]), "+f"(d[20]), "+f"(d[21]), "+f"(d[22]), "+f"(d[23]), "+f"(d[24]), "+f"(d[25]), "+f"(d[26]), "+f"(d[27]), "+f"(d[28]), "+f"(d[29]), "+f"(d[30]), "+f"(d[31]) : "l"(da), "l"(db), "r"(sd));
}
__device__ __forceinline__ void wgmma_n128_bt(float (&d)[64], uint64_t da, uint64_t db, int sd) {
  asm volatile("{.reg .pred p; setp.ne.b32 p, %66, 0;\n"
  "wgmma.mma_async.sync.aligned.m64n128k16.f32.bf16.bf16 {%0, %1, %2, %3, %4, %5, %6, %7, %8, %9, %10, %11, %12, %13, %14, %15, %16, %17, %18, %19, %20, %21, %22, %23, %24, %25, %26, %27, %28, %29, %30, %31, %32, %33, %34, %35, %36, %37, %38, %39, %40, %41, %42, %43, %44, %45, %46, %47, %48, %49, %50, %51, %52, %53, %54, %55, %56, %57, %58, %59, %60, %61, %62, %63}, %64, %65, p, 1, 1, 0, 1;}\n"
  : "+f"(d[0]), "+f"(d[1]), "+f"(d[2]), "+f"(d[3]), "+f"(d[4]), "+f"(d[5]), "+f"(d[6]), "+f"(d[7]), "+f"(d[8]), "+f"(d[9]), "+f"(d[10]), "+f"(d[11]), "+f"(d[12]), "+f"(d[13]), "+f"(d[14]), "+f"(d[15]), "+f"(d[16]), "+f"(d[17]), "+f"(d[18]), "+f"(d[19]), "+f"(d[20]), "+f"(d[21]), "+f"(d[22]), "+f"(d[23]), "+f"(d[24]), "+f"(d[25]), "+f"(d[26]), "+f"(d[27]), "+f"(d[28]), "+f"(d[29]), "+f"(d[30]), "+f"(d[31]), "+f"(d[32]), "+f"(d[33]), "+f"(d[34]), "+f"(d[35]), "+f"(d[36]), "+f"(d[37]), "+f"(d[38]), "+f"(d[39]), "+f"(d[40]), "+f"(d[41]), "+f"(d[42]), "+f"(d[43]), "+f"(d[44]), "+f"(d[45]), "+f"(d[46]), "+f"(d[47]), "+f"(d[48]), "+f"(d[49]), "+f"(d[50]), "+f"(d[51]), "+f"(d[52]), "+f"(d[53]), "+f"(d[54]), "+f"(d[55]), "+f"(d[56]), "+f"(d[57]), "+f"(d[58]), "+f"(d[59]), "+f"(d[60]), "+f"(d[61]), "+f"(d[62]), "+f"(d[63]) : "l"(da), "l"(db), "r"(sd));
}
__device__ __forceinline__ void wgmma_n176_bt(float (&d)[88], uint64_t da, uint64_t db, int sd) {
  asm volatile("{.reg .pred p; setp.ne.b32 p, %90, 0;\n"
  "wgmma.mma_async.sync.aligned.m64n176k16.f32.bf16.bf16 {%0, %1, %2, %3, %4, %5, %6, %7, %8, %9, %10, %11, %12, %13, %14, %15, %16, %17, %18, %19, %20, %21, %22, %23, %24, %25, %26, %27, %28, %29, %30, %31, %32, %33, %34, %35, %36, %37, %38, %39, %40, %41, %42, %43, %44, %45, %46, %47, %48, %49, %50, %51, %52, %53, %54, %55, %56, %57, %58, %59, %60, %61, %62, %63, %64, %65, %66, %67, %68, %69, %70, %71, %72, %73, %74, %75, %76, %77, %78, %79, %80, %81, %82, %83, %84, %85, %86, %87}, %88, %89, p, 1, 1, 0, 1;}\n"
  : "+f"(d[0]), "+f"(d[1]), "+f"(d[2]), "+f"(d[3]), "+f"(d[4]), "+f"(d[5]), "+f"(d[6]), "+f"(d[7]), "+f"(d[8]), "+f"(d[9]), "+f"(d[10]), "+f"(d[11]), "+f"(d[12]), "+f"(d[13]), "+f"(d[14]), "+f"(d[15]), "+f"(d[16]), "+f"(d[17]), "+f"(d[18]), "+f"(d[19]), "+f"(d[20]), "+f"(d[21]), "+f"(d[22]), "+f"(d[23]), "+f"(d[24]), "+f"(d[25]), "+f"(d[26]), "+f"(d[27]), "+f"(d[28]), "+f"(d[29]), "+f"(d[30]), "+f"(d[31]), "+f"(d[32]), "+f"(d[33]), "+f"(d[34]), "+f"(d[35]), "+f"(d[36]), "+f"(d[37]), "+f"(d[38]), "+f"(d[39]), "+f"(d[40]), "+f"(d[41]), "+f"(d[42]), "+f"(d[43]), "+f"(d[44]), "+f"(d[45]), "+f"(d[46]), "+f"(d[47]), "+f"(d[48]), "+f"(d[49]), "+f"(d[50]), "+f"(d[51]), "+f"(d[52]), "+f"(d[53]), "+f"(d[54]), "+f"(d[55]), "+f"(d[56]), "+f"(d[57]), "+f"(d[58]), "+f"(d[59]), "+f"(d[60]), "+f"(d[61]), "+f"(d[62]), "+f"(d[63]), "+f"(d[64]), "+f"(d[65]), "+f"(d[66]), "+f"(d[67]), "+f"(d[68]), "+f"(d[69]), "+f"(d[70]), "+f"(d[71]), "+f"(d[72]), "+f"(d[73]), "+f"(d[74]), "+f"(d[75]), "+f"(d[76]), "+f"(d[77]), "+f"(d[78]), "+f"(d[79]), "+f"(d[80]), "+f"(d[81]), "+f"(d[82]), "+f"(d[83]), "+f"(d[84]), "+f"(d[85]), "+f"(d[86]), "+f"(d[87]) : "l"(da), "l"(db), "r"(sd));
}
__device__ __forceinline__ void wgmma_qk_f16(float (&d)[32], uint64_t da, uint64_t db, int sd) {
  asm volatile("{.reg .pred p; setp.ne.b32 p, %34, 0;\n"
  "wgmma.mma_async.sync.aligned.m64n64k16.f32.f16.f16 {%0, %1, %2, %3, %4, %5, %6, %7, %8, %9, %10, %11, %12, %13, %14, %15, %16, %17, %18, %19, %20, %21, %22, %23, %24, %25, %26, %27, %28, %29, %30, %31}, %32, %33, p, 1, 1, 0, 0;}\n"
  : "+f"(d[0]), "+f"(d[1]), "+f"(d[2]), "+f"(d[3]), "+f"(d[4]), "+f"(d[5]), "+f"(d[6]), "+f"(d[7]), "+f"(d[8]), "+f"(d[9]), "+f"(d[10]), "+f"(d[11]), "+f"(d[12]), "+f"(d[13]), "+f"(d[14]), "+f"(d[15]), "+f"(d[16]), "+f"(d[17]), "+f"(d[18]), "+f"(d[19]), "+f"(d[20]), "+f"(d[21]), "+f"(d[22]), "+f"(d[23]), "+f"(d[24]), "+f"(d[25]), "+f"(d[26]), "+f"(d[27]), "+f"(d[28]), "+f"(d[29]), "+f"(d[30]), "+f"(d[31]) : "l"(da), "l"(db), "r"(sd));
}
__device__ __forceinline__ void wgmma_qk_bf16(float (&d)[32], uint64_t da, uint64_t db, int sd) {
  asm volatile("{.reg .pred p; setp.ne.b32 p, %34, 0;\n"
  "wgmma.mma_async.sync.aligned.m64n64k16.f32.bf16.bf16 {%0, %1, %2, %3, %4, %5, %6, %7, %8, %9, %10, %11, %12, %13, %14, %15, %16, %17, %18, %19, %20, %21, %22, %23, %24, %25, %26, %27, %28, %29, %30, %31}, %32, %33, p, 1, 1, 0, 0;}\n"
  : "+f"(d[0]), "+f"(d[1]), "+f"(d[2]), "+f"(d[3]), "+f"(d[4]), "+f"(d[5]), "+f"(d[6]), "+f"(d[7]), "+f"(d[8]), "+f"(d[9]), "+f"(d[10]), "+f"(d[11]), "+f"(d[12]), "+f"(d[13]), "+f"(d[14]), "+f"(d[15]), "+f"(d[16]), "+f"(d[17]), "+f"(d[18]), "+f"(d[19]), "+f"(d[20]), "+f"(d[21]), "+f"(d[22]), "+f"(d[23]), "+f"(d[24]), "+f"(d[25]), "+f"(d[26]), "+f"(d[27]), "+f"(d[28]), "+f"(d[29]), "+f"(d[30]), "+f"(d[31]) : "l"(da), "l"(db), "r"(sd));
}
__device__ __forceinline__ void wgmma_pv(float (&d)[12], uint32_t a0, uint32_t a1, uint32_t a2, uint32_t a3, uint64_t db) {
  asm volatile("wgmma.mma_async.sync.aligned.m64n24k16.f32.bf16.bf16 {%0, %1, %2, %3, %4, %5, %6, %7, %8, %9, %10, %11}, {%12, %13, %14, %15}, %16, 1, 1, 1, 1;\n"
  : "+f"(d[0]), "+f"(d[1]), "+f"(d[2]), "+f"(d[3]), "+f"(d[4]), "+f"(d[5]), "+f"(d[6]), "+f"(d[7]), "+f"(d[8]), "+f"(d[9]), "+f"(d[10]), "+f"(d[11]) : "r"(a0), "r"(a1), "r"(a2), "r"(a3), "l"(db));
}

#define PAT "LLMMIILLMILLIIMM"
__host__ __device__ constexpr char ptype(int i) { return PAT[i]; }
constexpr float INIT_L = 256.0f + 127.0f - 77.164f / 128.0f + 1.0f / 256.0f;
constexpr float INIT_I = 256.0f + 190.0f - 75.041f / 128.0f + 1.0f / 256.0f;
__host__ __device__ constexpr float initv(int i) { return ptype(i) == 'M' ? 0.0f : ptype(i) == 'L' ? INIT_L : INIT_I; }
__device__ __forceinline__ uint32_t exp_pair(char ty, float a, float b, uint32_t c1, uint32_t c2, uint32_t c3) {
  if (ty == 'M') return pack_bf16(ex2(a), ex2(b));
  uint32_t y = __byte_perm(__float_as_uint(a), __float_as_uint(b), 0x6521), m, e, r;
  if (ty == 'L') {
    asm("lop3.b32 %0, %1, 0x007F007F, %2, 0xEA;" : "=r"(m) : "r"(y), "r"(c1));
    asm("lop3.b32 %0, %1, 0x7F807F80, %2, 0xEA;" : "=r"(e) : "r"(y), "r"(c2));
  } else {
    asm("lop3.b32 %0, %1, 0x007F007F, %2, 0xEA;" : "=r"(m) : "r"(y), "r"(c3));
    e = y - m;
  }
  asm("fma.rn.bf16x2 %0, %1, %2, %3;" : "=r"(r) : "r"(y), "r"(m), "r"(e));
  return r;
}
template <int HF> __device__ __forceinline__ void exp_half(const float (&s)[32], uint32_t (&p)[8], uint32_t c1, uint32_t c2, uint32_t c3) {
#pragma unroll
  for (int i = HF * 8; i < HF * 8 + 8; i++) p[i - HF * 8] = exp_pair(ptype(i), s[2 * i], s[2 * i + 1], c1, c2, c3);
}

struct Params {
  CUtensorMap tx, twq, two, tw2;
  const __nv_bfloat16 *x, *wq, *wk, *wv, *wo, *w1, *w2;
  __nv_bfloat16* out;
  uint32_t c1, c2, c3;
};

constexpr uint64_t RING_PAR = 0x8d333fc0000ull;
__device__ __forceinline__ int k2_chunk(int j, int p) {
  const uint64_t t = j < 4 ? (j < 2 ? 0xa9754286310ull : 0xa9752186043ull) : (j < 6 ? 0xa9542183076ull : 0xa7542163098ull);
  return (int)(t >> (4 * p)) & 15;
}
__device__ __forceinline__ int f_start(int j) { int n4 = j >> 1; return 688 * (j & 1) + (n4 == 3 ? 512 : 176 * n4); }

__device__ __forceinline__ void load_w1(uint32_t sb, int j, int k) {
  bulk_g2s(sb + (uint32_t)((W1_SLOT >> (4 * k)) & 7) * 22 * KB, g_w1t + (j * 8 + k) * 22 * KB, 22 * KB, sb + OFF_BAR + 8 * (B_W1F + k));
}

__device__ __forceinline__ void region_freed(const Params& P, uint32_t sb, int it, bool duty) {
  const uint32_t bars = sb + OFF_BAR;
  uint32_t old = 0;
  if (elect_one()) {
    if (duty) {
      const int g = fresh_cta() >> 3;
      if (it == 0) {
        mbar_wait(bars + 8 * B_OA, 0);
        flag_add(C_O + g);
      } else if (it == 1) {
        asm volatile("cp.async.cg.shared.global [%0], [%1], 16;" ::"r"(sb + OFF_FL), "l"(&g_cnt[(C_O + g) * CNT_STRIDE]) : "memory");
        asm volatile("cp.async.cg.shared.global [%0], [%1], 16;" ::"r"(sb + OFF_FL + 16), "l"(&g_cnt[C_AUX * CNT_STRIDE]) : "memory");
      } else {
        asm volatile("cp.async.wait_all;" ::: "memory");
        mbar_wait(bars + 8 * B_F2, 0);
        const uint32_t e1 = lds32(sb + OFF_SC + 4 * SC_EPOCH) + 1;
        if ((int)((lds32(sb + OFF_FL) - e1 * 8) | (lds32(sb + OFF_FL + 16) - e1 * NAUX)) < 0) { flag_wait(C_O + g, e1 * 8); flag_wait(C_AUX, e1 * NAUX); }
        const int j = fresh_cta() & 7, n0 = min(j, 6) * 8 * KB;
        const uint8_t* src = g_act + (size_t)g * G_STRIDE + G_O;
        mbar_expect(bars + 8 * B_WO, 56 * KB);
        if (j) bulk_g2s(sb + OFF_RING, src, n0, bars + 8 * B_WO);
        if (j < 6) bulk_g2s(sb + OFF_RING + n0, src + n0 + 8 * KB, 48 * KB - n0, bars + 8 * B_WO);
        bulk_g2s(sb + 44 * KB, src + (j == 7 ? 48 : 56) * KB, 8 * KB, bars + 8 * B_WO);
      }
    }
    if (it == 1) mbar_arrive(bars + 8 * B_F2);
    else if (it == 2) {
      asm volatile("atom.relaxed.cta.shared::cta.add.u32 %0, [%1], 1;" : "=r"(old) : "r"(sb + OFF_SC + 4 * SC_FREE) : "memory");
      if (old == 15) {
        const int j = fresh_cta() & 7;
        mbar_expect(bars + 8 * B_WO, 64 * KB);
        tma2d(sb + OFF_WO, &P.two, 64 * j, 0, bars + 8 * B_WO);
        tma2d(sb + OFF_WO + 32 * KB, &P.two, 64 * j, 256, bars + 8 * B_WO);
        mbar_expect(bars + 8 * B_W1F, 44 * KB);
        bulk_g2s(sb, g_w1t + j * 176 * KB, 44 * KB, bars + 8 * B_W1F);
      }
    }
  }
  __syncwarp();
}

__device__ __forceinline__ void publish_o(const float (&o)[12], uint32_t sb, int t, int wg, bool storer) {
  float i0, i1;
  asm("rcp.approx.ftz.f32 %0, %1;" : "=f"(i0) : "f"(o[8]));
  asm("rcp.approx.ftz.f32 %0, %1;" : "=f"(i1) : "f"(o[10]));
  const uint32_t stg = sb + OFF_Q + (t * 4 + wg) * 2048;
  const int tid = fresh_tid(), cta = fresh_cta();
  const uint32_t p0 = pack_bf16(o[0] * i0, o[1] * i0), p1 = pack_bf16(o[2] * i1, o[3] * i1), p2 = pack_bf16(o[4] * i0, o[5] * i0), p3 = pack_bf16(o[6] * i1, o[7] * i1);
  uint8_t* dst = g_act + (size_t)(cta >> 3) * G_STRIDE + G_O + t * 65536 + (8 * (cta & 7) + 2 * wg) * 1024;
  dst += (tid & 96) * 8 + (tid & 31) * 4;
  stg32(dst, p0); stg32(dst + 128, p1); stg32(dst + 1024, p2); stg32(dst + 1152, p3);
  if (t && elect_one()) hint_add(C_OB + (cta >> 3), cta & 7);
  stsm4(stg + stsm_off(tid), p0, p1, p2, p3);
  fence_async_smem();
  if (storer && t == 0) asm volatile("cp.async.bulk.commit_group;\ncp.async.bulk.wait_group 0;" ::: "memory");
  __syncwarp();
  if (elect_one()) { mbar_arrive(sb + OFF_BAR + 8 * (t ? B_ADONE : B_OA)); if (t && storer) TSTAMP(32 + wg); }
  __syncwarp();
}
__device__ __forceinline__ void start_fills(uint32_t sb, int wg, bool storer) {
  if (storer) {
    if (elect_one()) {
      const int cta = fresh_cta(), j = cta & 7, hf = wg & 1;
      uint8_t* act = g_act + (size_t)(cta >> 3) * G_STRIDE;
      bulk_s2g(act + G_O + 65536 + (8 * j + 2 * wg) * 1024, sb + OFF_FILL, 2048);
      bulk_s2g(act + (wg < 2 ? G_H + (hf * 8 + j) * 8192 : G_HH + (hf * 172 + (f_start(j) >> 3)) * 1024), sb + OFF_FILL, wg < 2 ? 8 * KB : 22 * KB);
      if (wg < 2) bulk_s2g(act + G_ST + (hf * 8 + j) * 512, sb + OFF_FILL, 512);
    }
    __syncwarp();
  }
}
__device__ __forceinline__ void attention_fast(const Params& P, uint32_t sb, int wg, int duty, bool storer) {
  uint32_t c1 = P.c1, c2 = P.c2, c3 = P.c3;
  asm volatile("" : "+r"(c1), "+r"(c2), "+r"(c3));
#pragma unroll 1
  for (int t = 0; t < 2; t++) {
    float o[12], sA[32], sB[32];
    uint32_t pX[8], pY[8];
    const uint64_t dQ = mkdesc(sb + OFF_Q + (t * 4 + wg) * 2048, 1024, 128);
    uint64_t dK = mkdesc(sb, 4096, 128), dV = mkdesc(sb + 8192, 128, 4096);
#pragma unroll
    for (int i = 0; i < 12; i++) o[i] = 0.f;
#pragma unroll
    for (int i = 0; i < 16; i++) { sA[2 * i] = sA[2 * i + 1] = sB[2 * i] = sB[2 * i + 1] = initv(i); }
    pin(o); pin(sA); pin(sB);
    if (t == 0) mbar_wait(sb + OFF_BAR + 8 * B_KV0, 0);
    wg_fence();
    wgmma_qk_f16(sA, dQ, dK, 1);
    wgmma_qk_f16(sB, dQ, dK + 64, 1);
    wg_commit();
    if (t == 0) start_fills(sb, wg, storer);
    wg_wait<0>();
#pragma unroll 1
    for (int it = 0; it < 4; it++) {
      pin(sA); pin(sB);
#pragma unroll
      for (int j = 0; j < 8; j++) {
        float(&s)[32] = (j & 1) ? sB : sA;
        const int voff = (j >> 2) * (CHB / 16) + (j & 3) * 64, koff = ((j + 2) >> 2) * (CHB / 16) + ((j + 2) & 3) * 64;
        if (j > 0) wg_wait<1>();
        pin(s); pin(pX);
        exp_half<0>(s, pX, c1, c2, c3);
        pin(pX);
        wg_fence();
        wgmma_pv(o, pX[0], pX[1], pX[2], pX[3], dV + voff);
        wgmma_pv(o, pX[4], pX[5], pX[6], pX[7], dV + voff + 16);
        wg_commit();
        if (j > 0) wg_wait<1>();
        pin(pY);
        exp_half<1>(s, pY, c1, c2, c3);
        pin(pY);
        wg_fence();
        wgmma_pv(o, pY[0], pY[1], pY[2], pY[3], dV + voff + 32);
        wgmma_pv(o, pY[4], pY[5], pY[6], pY[7], dV + voff + 48);
        wgmma_qk_f16(s, dQ, dK + koff, 1);
        wg_commit();
      }
      dK += 2 * (CHB / 16); dV += 2 * (CHB / 16);
      wg_wait<0>();
      if (t == 0) { if (it == 0) mbar_wait(sb + OFF_BAR + 8 * B_KV1, 0); }
      else if (it < 3 && (it || duty)) region_freed(P, sb, it, duty & (it ? 2 : 1));
    }
    pin(o); pin(pX); pin(pY);
    publish_o(o, sb, t, wg, storer);
  }
}

__device__ __forceinline__ void attention_safe(const Params& P, uint32_t sb, int wg, int duty, bool storer) {
  start_fills(sb, wg, storer);
#pragma unroll 1
  for (int t = 0; t < 2; t++) {
    float o[12], s[32], m0 = -INFINITY, m1 = -INFINITY;
    uint32_t p[16];
    const uint64_t dQ = mkdesc(sb + OFF_Q + (t * 4 + wg) * 2048, 1024, 128);
#pragma unroll
    for (int i = 0; i < 12; i++) o[i] = 0.f;
#pragma unroll
    for (int i = 0; i < 32; i++) s[i] = 0.f;
#pragma unroll 1
    for (int j = 0; j < 32; j++) {
      const uint32_t base = sb + (j >> 2) * CHB + (j & 3) * 1024;
      pin(s);
      wg_fence();
      wgmma_qk_bf16(s, dQ, mkdesc(base, 4096, 128), 0);
      wg_commit();
      wg_wait<0>();
      pin(s);
      float n0 = m0, n1 = m1;
#pragma unroll
      for (int i = 0; i < 16; i++) {
        const uint32_t r = pack_bf16(s[2 * i], s[2 * i + 1]);
        s[2 * i] = bf_lo(r); s[2 * i + 1] = bf_hi(r);
        if (i & 1) n1 = fmaxf(n1, fmaxf(s[2 * i], s[2 * i + 1])); else n0 = fmaxf(n0, fmaxf(s[2 * i], s[2 * i + 1]));
      }
      n0 = fmaxf(n0, __shfl_xor_sync(~0u, n0, 1)); n0 = fmaxf(n0, __shfl_xor_sync(~0u, n0, 2));
      n1 = fmaxf(n1, __shfl_xor_sync(~0u, n1, 1)); n1 = fmaxf(n1, __shfl_xor_sync(~0u, n1, 2));
      const float r0 = ex2((m0 - n0) * QK_SCALE_LOG2), r1 = ex2((m1 - n1) * QK_SCALE_LOG2);
      m0 = n0; m1 = n1;
#pragma unroll
      for (int i = 0; i < 12; i++) o[i] *= (i & 2) ? r1 : r0;
#pragma unroll
      for (int i = 0; i < 16; i++) {
        const float mm = (i & 1) ? m1 : m0;
        p[i] = pack_bf16(ex2((s[2 * i] - mm) * QK_SCALE_LOG2), ex2((s[2 * i + 1] - mm) * QK_SCALE_LOG2));
      }
      pin(o); pin(p);
      wg_fence();
      const uint64_t dV = mkdesc(base + 8192, 128, 4096);
#pragma unroll
      for (int k = 0; k < 4; k++) wgmma_pv(o, p[4 * k], p[4 * k + 1], p[4 * k + 2], p[4 * k + 3], dV + 16 * k);
      wg_commit();
      wg_wait<0>();
      pin(o); pin(p);
      if (t == 1 && (j & 7) == 7 && j < 24) region_freed(P, sb, j >> 3, duty & (j > 7 ? 2 : 1));
    }
    publish_o(o, sb, t, wg, storer);
  }
}

__device__ __forceinline__ void aux_cta(const Params& P, uint8_t* smem) {
  const int a = blockIdx.x - NMAIN, tid = threadIdx.x, warp = tid >> 5, lane = tid & 31;
  const uint32_t sb = s2u(smem), bars = sb + OFF_BAR;
  { const long long t0 = clock64(); while (clock64() - t0 < 3000) {} }
  constexpr int PITCH = 43 * 16;
  if (tid == 0) {
#pragma unroll
    for (int i = 0; i < 4; i++) mbar_init(bars + 8 * i, 128);
  }
  fence_async_smem();
  __syncthreads();
  const int rr = warp * 8 + (lane & 7);
  const __nv_bfloat16* wsrc = P.w1 + (size_t)rr * F_ + a * 344;
  if (lane < 16) {
    mbar_expect(bars + (lane & 8), 688);
    bulk_g2s(sb + ((lane >> 3) * 128 + rr) * PITCH, wsrc + (lane >> 3) * 128 * F_, 688, bars + (lane & 8));
  }
  if (tid == 0) TSTAMP(1);
  float acc[3][8];
#pragma unroll
  for (int q = 0; q < 3; q++)
#pragma unroll
    for (int i = 0; i < 8; i++) acc[q][i] = 0.f;
#pragma unroll 1
  for (int h = 0; h < 4; h++) {
    mbar_wait(bars + 8 * h, 0);
#pragma unroll
    for (int q = 0; q < 3; q++) {
      const int blk = warp + 16 * q;
      if (blk < 43) {
        const int hb = (a & 1) * 43 + blk, n4 = min(hb / 22, 3);
        const int d0 = ((2 * n4 + (a >> 1)) * 176 + hb - (n4 == 3 ? 64 : 22 * n4)) * KB;
        const int d1 = (hb == 64 || hb == 65) ? ((6 + (a >> 1)) * 176 + hb - 64) * KB : -1;
#pragma unroll
        for (int u = 0; u < 4; u++) {
          const int r = u * 32 + lane;
          const uint4 w = *(const uint4*)(smem + ((h & 1) * 128 + r) * PITCH + blk * 16);
          uint8_t* dst = g_w1t + (h * 2 + (u >> 1)) * 22 * KB + (r & 63) * 16;
          *(uint4*)(dst + d0) = w;
          if (d1 >= 0) *(uint4*)(dst + d1) = w;
          acc[q][0] += bf_lo(w.x); acc[q][1] += bf_hi(w.x); acc[q][2] += bf_lo(w.y); acc[q][3] += bf_hi(w.y);
          acc[q][4] += bf_lo(w.z); acc[q][5] += bf_hi(w.z); acc[q][6] += bf_lo(w.w); acc[q][7] += bf_hi(w.w);
        }
      }
    }
    __syncthreads();
    if (h < 2 && lane < 8) {
      mbar_expect(bars + 8 * (h + 2), 688);
      bulk_g2s(sb + (h * 128 + rr) * PITCH, wsrc + (h + 2) * 128 * F_, 688, bars + 8 * (h + 2));
    }
    if (h == 2 && lane == 0) {
      l2_prefetch((const uint8_t*)P.wo + (size_t)(a * 16 + warp) * 8192, 8192);
      l2_prefetch((const uint8_t*)P.w2 + (size_t)(a * 16 + warp) * 22016, 22016);
    }
  }
  if (tid == 0) TSTAMP(2);
#pragma unroll
  for (int q = 0; q < 3; q++) {
#pragma unroll
    for (int i = 0; i < 8; i++)
#pragma unroll
      for (int o = 1; o < 32; o <<= 1) acc[q][i] += __shfl_xor_sync(~0u, acc[q][i], o);
    if (warp + 16 * q < 43 && lane == 0) {
      *(float4*)(g_cs1 + a * 344 + (warp + 16 * q) * 8) = make_float4(acc[q][0], acc[q][1], acc[q][2], acc[q][3]);
      *(float4*)(g_cs1 + a * 344 + (warp + 16 * q) * 8 + 4) = make_float4(acc[q][4], acc[q][5], acc[q][6], acc[q][7]);
    }
  }
  __syncthreads();
  if (tid == 0) { flag_add(C_AUX); flag_add(C_DONE); TSTAMP(0); }
}

__device__ __forceinline__ void kv_path(uint8_t* smem, uint32_t sb, const uint4 (&xr)[4]) {
  const int t = threadIdx.x - 256, w = t >> 5, lane = t & 31, g8 = lane >> 2, c = lane & 3;
  uint32_t xa[16] = {xr[0].x, xr[0].y, xr[0].z, xr[0].w, xr[2].x, xr[2].y, xr[2].z, xr[2].w,
                     xr[1].x, xr[1].y, xr[1].z, xr[1].w, xr[3].x, xr[3].y, xr[3].z, xr[3].w};
  if (c & 1) {
#pragma unroll
    for (int i = 0; i < 16; i += 2) { const uint32_t tmp = xa[i]; xa[i] = xa[i + 1]; xa[i + 1] = tmp; }
  }
  float s0 = 0, q0 = 0, s1 = 0, q1 = 0;
#pragma unroll
  for (int i = 0; i < 8; i++) {
    float a = bf_lo(xa[i]), b = bf_hi(xa[i]); s0 += a + b; q0 = fmaf(a, a, fmaf(b, b, q0));
    a = bf_lo(xa[8 + i]); b = bf_hi(xa[8 + i]); s1 += a + b; q1 = fmaf(a, a, fmaf(b, b, q1));
  }
  s0 += __shfl_xor_sync(~0u, s0, 1); q0 += __shfl_xor_sync(~0u, q0, 1); s1 += __shfl_xor_sync(~0u, s1, 1); q1 += __shfl_xor_sync(~0u, q1, 1);
  s0 += __shfl_xor_sync(~0u, s0, 2); q0 += __shfl_xor_sync(~0u, q0, 2); s1 += __shfl_xor_sync(~0u, s1, 2); q1 += __shfl_xor_sync(~0u, q1, 2);
  uint8_t* stg = g_kv + blockIdx.x * 16;
  float4* pst = (float4*)(smem + OFF_KVS);
  if (c == 0) pst[w * 8 + g8] = make_float4(s0, q0, s1, q1);
  bar_sync(12, 288);
  {
    const float4 u = pst[c * 16 + g8], v = pst[c * 16 + 8 + g8];
    s0 = u.x + v.x; q0 = u.y + v.y; s1 = u.z + v.z; q1 = u.w + v.w;
  }
  s0 += __shfl_xor_sync(~0u, s0, 1); q0 += __shfl_xor_sync(~0u, q0, 1); s1 += __shfl_xor_sync(~0u, s1, 1); q1 += __shfl_xor_sync(~0u, q1, 1);
  s0 += __shfl_xor_sync(~0u, s0, 2); q0 += __shfl_xor_sync(~0u, q0, 2); s1 += __shfl_xor_sync(~0u, s1, 2); q1 += __shfl_xor_sync(~0u, q1, 2);
  const float mean0 = s0 * (1.0f / D_), rstd0 = rsqrtf(fmaxf(q0 * (1.0f / D_) - mean0 * mean0, 0.f) + LN_EPS);
  const float mean1 = s1 * (1.0f / D_), rstd1 = rsqrtf(fmaxf(q1 * (1.0f / D_) - mean1 * mean1, 0.f) + LN_EPS);
  if (w == 0 && c == 0) {
    *(float2*)(stg + (R_ST + (g8 >> 1)) * 2048 + (g8 & 1) * 8) = make_float2(mean0, rstd0);
    *(float2*)(stg + (R_ST + 4 + (g8 >> 1)) * 2048 + (g8 & 1) * 8) = make_float2(mean1, rstd1);
  }
  float d[4][4], e[4][4];
#pragma unroll
  for (int i = 0; i < 4; i++)
#pragma unroll
    for (int k = 0; k < 4; k++) { d[i][k] = 0.f; e[i][k] = 0.f; }
  const uint32_t one = 0x3F803F80u;
  const uint32_t la = sb + OFF_WKV + (64 * w + 8 * ((lane & 7) >> 1) + 2 * (((lane >> 3) ^ (lane >> 1)) & 1) + (lane & 1)) * 32 + (((lane >> 4) ^ (lane >> 2)) & 1) * 16;
  mbar_wait(sb + OFF_BAR + 8 * B_WKV, 0);
  if (t == 0) TSTAMP(23);
#pragma unroll
  for (int ks = 0; ks < 4; ks++) {
    const uint32_t a0 = xa[2 * ks], a1 = xa[8 + 2 * ks], a2 = xa[2 * ks + 1], a3 = xa[9 + 2 * ks];
#pragma unroll
    for (int m = 0; m < 2; m++) {
      uint32_t bw[4];
      ldsm4t(bw, la + (32 * (ks >> 1) + 4 * (ks & 1)) * 32 + m * 16 * KB);
      const uint32_t b0 = c & 2 ? bw[2] : bw[0], b1 = c & 2 ? bw[3] : bw[1], b2 = c & 2 ? bw[0] : bw[2], b3 = c & 2 ? bw[1] : bw[3];
      mma16816(d[2 * m], a0, a1, a2, a3, b0, b1); mma16816(d[2 * m + 1], a0, a1, a2, a3, b2, b3);
      mma16816(e[2 * m], one, one, one, one, b0, b1); mma16816(e[2 * m + 1], one, one, one, one, b2, b3);
    }
  }
  __syncwarp();
  float* pw = (float*)(smem + OFF_WKV + w * 2048) + g8 * 18 + 2 * c;
#pragma unroll
  for (int i = 0; i < 4; i++) {
    *(float2*)(pw + (i >> 1) * 4096 + (i & 1) * 8) = make_float2(rstd0 * (d[i][0] - mean0 * e[i][0]), rstd0 * (d[i][1] - mean0 * e[i][1]));
    *(float2*)(pw + (i >> 1) * 4096 + (i & 1) * 8 + 144) = make_float2(rstd1 * (d[i][2] - mean1 * e[i][0]), rstd1 * (d[i][3] - mean1 * e[i][1]));
  }
  bar_sync(1, 256);
  const int row = lane & 15, cp = (2 * w + (lane >> 4)) & 7;
  float ax = 0, ay = 0;
  const float* pr = (const float*)(smem + OFF_WKV) + (w >> 2) * 4096 + 2 * cp + row * 18;
#pragma unroll
  for (int i = 0; i < 8; i++) { const float2 a = *(const float2*)(pr + i * 512); ax += a.x; ay += a.y; }
  uint32_t val = pack_bf16(ax, ay);
  float v0 = bf_lo(val), v1 = bf_hi(val);
  float nn = v0 * v0 + v1 * v1;
  nn += __shfl_xor_sync(~0u, nn, 16);
  const int sub = (cp >> 2) * 2 + (row & 1);
  if (w < 4) {
    *(uint32_t*)(stg + (R_KP + (row >> 1) * 4 + sub) * 2048 + (cp & 3) * 4) = val;
    const float m = fmaxf(fabsf(v0), fabsf(v1));
    const float m3 = fmaxf(m, fmaxf(__shfl_up_sync(~0u, m, 1, 16), __shfl_down_sync(~0u, m, 1, 16)));
    const float magic = __uint_as_float((__float_as_uint(m3) & 0x7F800000u) + (14u << 23) + 0x00400000u);
    v0 = (v0 + magic) - magic; v1 = (v1 + magic) - magic;
    const float p0 = __shfl_up_sync(~0u, v0, 1, 16), p1 = __shfl_up_sync(~0u, v1, 1, 16);
    val = row ? pack_f16(v0 - p0, v1 - p1) : pack_f16(v0, v1);
  } else if (cp < 4) {
    *(uint32_t*)(stg + ((row >> 1) * 10 + 8 + (row & 1)) * 2048 + cp * 4) = 0x3F803F80u;
  }
  *(uint32_t*)(stg + ((row >> 1) * 10 + (w >> 2) * 4 + sub) * 2048 + (cp & 3) * 4) = val;
  const uint32_t nmax = __reduce_max_sync(~0u, __float_as_uint(nn));
  if (lane == 0) *(uint32_t*)(stg + (R_MX + (w >> 2)) * 2048 + (w & 3) * 4) = nmax;
  bar_sync(7, 320);
}

__device__ __forceinline__ void post_chain(const Params& P, uint8_t* smem, uint32_t sb, int hf) {
  const int tid = fresh_tid() & 127, warp = tid >> 5, lane = tid & 31, g8 = lane >> 2, c = lane & 3;
  const int cta = fresh_cta(), g = cta >> 3, j = cta & 7, gh = g * 2 + hf;
  const uint32_t bars = sb + OFF_BAR;
  const int row0 = g * 128 + hf * 64 + warp * 16 + g8;
  uint8_t* act = g_act + (size_t)g * G_STRIDE;
  const int frag = warp * 256 + lane * 4;
  const bool lead = elect_one();
  const uint32_t rf = bars + 8 * (B_RF + 6 * hf);
  const uint64_t dA = mkdesc(sb, 1024, 128);
  if (tid == 0) mbar_expect(bars + 8 * (B_RED + hf), 16 * KB);
  {
    uint32_t xr[16];
    const uint32_t* xp = (const uint32_t*)(P.x + (size_t)row0 * D_ + 64 * j + 2 * c);
#pragma unroll
    for (int b = 0; b < 8; b++) { xr[2 * b] = __ldg(xp + 4 * b); xr[2 * b + 1] = __ldg(xp + 8 * 256 + 4 * b); }
    float acc[32];
    undef(acc);
    mbar_wait2(bars + 8 * (hf ? B_ADONE : B_WO), 0, bars + 8 * B_WO);
    if (tid == 0 && hf == 0) TSTAMP(29);
    const uint64_t dw = mkdesc(sb + OFF_WO, 8192, 1024, 1);
    wg_fence();
#pragma unroll
    for (int s = 0; s < 4; s++) wgmma_n64_bt(acc, dA + ((OFF_Q + hf * 8 * KB) >> 4) + 128 * s, dw + 512 * j + 128 * s, s);
    wg_commit();
#pragma unroll
    for (int k = 0; k < 7; k++) {
      const int u = hf ? k : (k + 6) % 7;
      const uint64_t da = dA + (u == 6 ? 44 * 64 : (hf ? 120 * 64 : OFF_RING >> 4) + 512 * u), db = dw + 512 * (u < j ? u : u + 1);
      if (hf) mbar_wait(k < 6 ? rf + 8 * k : bars + 8 * B_OX, 0);
      else { wg_wait<0>(); if (k == 1 && lead) mbar_arrive(bars + 8 * B_OWN); }
      wg_fence();
#pragma unroll
      for (int s = 0; s < 4; s++) wgmma_n64_bt(acc, da + 128 * s, db + 128 * s, 1);
      wg_commit();
    }
    wg_wait<0>();
    pin(acc);
    if (lane < 7 && (lane == 6 || !hf)) mbar_arrive(bars + 8 * (lane < 6 ? B_RE + lane : B_PDONE));
    redo_gemm<8>(acc, act + G_O + hf * 65536 + (warp * 16 + g8) * 16, D_, P.wo + 64 * j + 2 * c, D_, 0);
    if (tid == 0) TSTAMP(30 + hf);
#pragma unroll
    for (int b = 0; b < 8; b++) {
      xr[2 * b] = pack_bf16(acc[4 * b] + bf_lo(xr[2 * b]), acc[4 * b + 1] + bf_hi(xr[2 * b]));
      xr[2 * b + 1] = pack_bf16(acc[4 * b + 2] + bf_lo(xr[2 * b + 1]), acc[4 * b + 3] + bf_hi(xr[2 * b + 1]));
      stg32(act + G_H + (hf * 8 + j) * 8192 + frag + b * 1024, xr[2 * b]);
      stg32(act + G_H + (hf * 8 + j) * 8192 + frag + b * 1024 + 128, xr[2 * b + 1]);
    }
    if (lead) { hint_add(C_H + gh, j); mbar_arrive(bars + 8 * (B_SA + hf)); if (warp == 3) TSTAMP(40 + hf); }
    __syncwarp();
    pin(xr);
    float s0 = 0, q0 = 0, s1 = 0, q1 = 0;
#pragma unroll
    for (int b = 0; b < 8; b++) {
      float u = bf_lo(xr[2 * b]), v = bf_hi(xr[2 * b]); s0 += u + v; q0 = fmaf(u, u, fmaf(v, v, q0));
      u = bf_lo(xr[2 * b + 1]); v = bf_hi(xr[2 * b + 1]); s1 += u + v; q1 = fmaf(u, u, fmaf(v, v, q1));
    }
    s0 += __shfl_xor_sync(~0u, s0, 1); q0 += __shfl_xor_sync(~0u, q0, 1); s1 += __shfl_xor_sync(~0u, s1, 1); q1 += __shfl_xor_sync(~0u, q1, 1);
    s0 += __shfl_xor_sync(~0u, s0, 2); q0 += __shfl_xor_sync(~0u, q0, 2); s1 += __shfl_xor_sync(~0u, s1, 2); q1 += __shfl_xor_sync(~0u, q1, 2);
    stg32(act + G_ST + (hf * 8 + j) * 512 + tid * 4, __float_as_uint(c == 0 ? s0 : c == 1 ? q0 : c == 2 ? s1 : q1));
  }
  if (tid == 0) TSTAMP(8 + hf * 8);
  {
    float acc[88];
    undef(acc);
#define RSLOT(r0, r1) ((r0) % 6 + hf * ((r1) % 6 - (r0) % 6))
#define RPAR(r0, r1) ((int)(RING_PAR >> (r0) & 1) + hf * ((int)(RING_PAR >> (r1) & 1) - (int)(RING_PAR >> (r0) & 1)))
    const uint64_t dR = dA + (OFF_RING >> 4), dW = mkdesc(sb, 128, 1024);
    mbar_wait2(rf + 8 * RSLOT(12, 20), RPAR(12, 20), bars + 8 * B_W1F);
    if (tid == 0) TSTAMP(13 + hf * 8);
    wg_fence();
#pragma unroll
    for (int k = 0; k < 8; k++) {
      const uint64_t da = dR + 512 * RSLOT(12 + k, 20 + k), db = dW + ((W1_SLOT >> (4 * k)) & 7) * 1408;
      wgmma_n176_bt(acc, da, db, k);
      wgmma_n176_bt(acc, da + 128, db + 16, 1);
      wg_commit();
      if (k > 0) {
        wg_wait<1>();
        if (lane < 2) mbar_arrive(bars + 8 * (lane ? B_W1E + k - 1 : B_RE + RSLOT(11 + k, 19 + k)));
      }
      wgmma_n176_bt(acc, da + 256, db + 32, 1);
      wg_commit();
      if (k < 7) mbar_wait2(rf + 8 * RSLOT(13 + k, 21 + k), RPAR(13 + k, 21 + k), bars + 8 * (B_W1F + k + 1));
      wg_fence();
      wgmma_n176_bt(acc, da + 384, db + 48, 1);
      wg_commit();
    }
    mbar_wait(bars + 8 * (B_ST2 + hf), 0);
    const float4 ln = *(const float4*)(smem + OFF_ST2 + hf * 512 + (tid >> 2) * 16);
    const float hr0 = ln.x, m0 = ln.y, hr1 = ln.z, m1 = ln.w;
    wg_wait<0>();
    pin(acc);
    if (lane < 2) mbar_arrive(bars + 8 * (lane ? B_W1E + 7 : B_RE + RSLOT(19, 27)));
    redo_gemm<22>(acc, act + G_H + hf * 65536 + (warp * 16 + g8) * 16, D_, P.w1 + f_start(j) + 2 * c, F_, 0);
    if (tid == 0) TSTAMP(9 + hf * 8);
    const float2* cs = (const float2*)(smem + OFF_CS) + c;
    const uint32_t stg = sb + (hf ? 110 * KB : 0);
    uint32_t hp[12];
    uint8_t* hdst = act + G_HH + (hf * 172 + (f_start(j) >> 3)) * 1024 + frag;
    float2 cn[4] = {cs[0], cs[4], cs[8], cs[12]};
#pragma unroll
    for (int b = 0; b < 22; b++) {
      const float2 cc = cn[b & 3];
      if (b + 4 < 22) cn[b & 3] = cs[4 * (b + 4)];
      float v[4] = {fmaf(acc[4 * b], hr0, m0 * cc.x), fmaf(acc[4 * b + 1], hr0, m0 * cc.y),
                    fmaf(acc[4 * b + 2], hr1, m1 * cc.x), fmaf(acc[4 * b + 3], hr1, m1 * cc.y)};
#pragma unroll
      for (int i = 0; i < 4; i++) {
        float th; asm("tanh.approx.f32 %0, %1;" : "=f"(th) : "f"(v[i]));
        v[i] = fmaf(v[i], th, v[i]);
      }
      const int q = b < 6 ? 2 * b : 2 * (b & 1);
      hp[q] = pack_bf16(v[0], v[1]);
      hp[q + 1] = pack_bf16(v[2], v[3]);
      stg32(hdst + b * 1024, hp[q]); stg32(hdst + b * 1024 + 128, hp[q + 1]);
      if ((b == 11 || b == 21) && lead) {
        hint_add(C_HH + gh, j + (b == 11 ? 8 : 0));
        mbar_arrive(bars + 8 * ((b == 11 ? B_S1 : B_SH) + hf));
        if (warp == 3) TSTAMP((b == 11 ? 56 : 42) + hf);
      }
      if (b == 5) {
        pin(hp);
        mbar_wait(bars + 8 * (B_W1E + 7 * hf), 0);
#pragma unroll
        for (int s = 0; s < 3; s++) stsm4(stg + stsm_off(tid) + s * 2048, hp[4 * s], hp[4 * s + 1], hp[4 * s + 2], hp[4 * s + 3]);
      } else if (b > 5 && b < 20 && (b & 1)) {
        stsm4(stg + stsm_off(tid) + (b >> 1) * 2048, hp[0], hp[1], hp[2], hp[3]);
      }
    }
    fence_async_smem();
  }
  if (tid == 0) TSTAMP(10 + hf * 8);
  {
    float acc[64];
    undef(acc);
    uint32_t hr[16];
    const uint8_t* himg = act + G_H + (hf * 8 + j) * 8192 + frag;
#pragma unroll
    for (int b = 0; b < 8; b++) { hr[2 * b] = __ldcg((const uint32_t*)(himg + b * 1024)); hr[2 * b + 1] = __ldcg((const uint32_t*)(himg + b * 1024 + 128)); }
    const int kh = j & 1;
    uint32_t peer;
    asm volatile("mapa.shared::cluster.u32 %0, %1, %2;" : "=r"(peer) : "r"(sb), "r"(kh ^ 1));
    const uint64_t dR = dA + (OFF_RING >> 4), dW = mkdesc(sb, 0, 1024, 1);
    {
      const uint64_t da = dA + (hf ? 110 * 64 : 0) + (4 * k2_chunk(j, 0) - (f_start(j) - 688 * kh) / 16) * 128;
      mbar_wait2(bars + 8 * B_W2F, 0, bars + 8 * (B_W2F + 1));
      wg_fence();
#pragma unroll
      for (int s = 0; s < 8; s++) wgmma_n128_bt(acc, da + 128 * s, dW + ((s < 4 ? 3 : 17) * 512 + (1 << 25) + 128 * (s & 3)), s);
      wg_commit();
      wg_wait<0>();
      if (lead) {
        mbar_arrive(bars + 8 * (B_SW + hf));
        asm volatile("mbarrier.arrive.relaxed.cluster.shared::cluster.b64 _, [%0];" ::"r"(peer + OFF_BAR + 8 * B_LAND) : "memory");
      }
    }
    mbar_wait2(rf + 8 * RSLOT(28, 37), RPAR(28, 37), bars + 8 * (B_W2F + 2));
    if (tid == 0) TSTAMP(14 + hf * 8);
    wg_fence();
#pragma unroll
    for (int i = 2; i < 11; i++) {
      const uint32_t a0 = (uint32_t)(W2_A0 >> (5 * i)) & 31, a1 = (uint32_t)(W2_A1 >> (5 * i)) & 31;
      const uint64_t da = dR + 512 * RSLOT(26 + i, 35 + i), db = dW + (a0 * 512 + ((a1 - a0) << 25));
      wgmma_n128_bt(acc, da, db, 1);
      wgmma_n128_bt(acc, da + 128, db + 128, 1);
      wg_commit();
      if (i > 2) {
        wg_wait<1>();
        if (lead) mbar_arrive(bars + 8 * (B_RE + RSLOT(25 + i, 34 + i)));
      }
      wgmma_n128_bt(acc, da + 256, db + 256, 1);
      wg_commit();
      if (i < 10) {
        mbar_wait2(rf + 8 * RSLOT(27 + i, 36 + i), RPAR(27 + i, 36 + i), bars + 8 * (B_W2F + i + 1));
        wg_fence();
        wgmma_n128_bt(acc, da + 384, db + 384, 1);
        wg_commit();
      }
    }
    mbar_wait(bars + 8 * B_LAND, 0);
    wg_wait<0>();
    pin(acc);
    redo_gemm<16>(acc, act + G_HH + (hf * 172 + kh * 86) * 1024 + (warp * 16 + g8) * 16, 688, P.w2 + (size_t)kh * 688 * D_ + 64 * j + 2 * c, D_, -128 * kh);
    if (tid == 0) TSTAMP(11 + hf * 8);
    const uint32_t land = (hf ? 136 : 24) * KB + tid * 16;
#pragma unroll
    for (int i = 0; i < 8; i++)
      asm volatile("st.async.shared::cluster.mbarrier::complete_tx::bytes.v4.f32 [%0], {%1,%2,%3,%4}, [%5];"
                   ::"r"(peer + land + i * 2048), "f"(acc[32 + 4 * i]), "f"(acc[33 + 4 * i]), "f"(acc[34 + 4 * i]), "f"(acc[35 + 4 * i]),
                     "r"(peer + OFF_BAR + 8 * (B_RED + hf)) : "memory");
    if (lead) mbar_arrive(bars + 8 * (B_RE + RSLOT(36, 45)));
    if (tid == 0) TSTAMP(58 + hf);
#pragma unroll
    for (int i = 0; i < 8; i++) {
      acc[4 * i] += bf_lo(hr[2 * i]); acc[4 * i + 1] += bf_hi(hr[2 * i]); acc[4 * i + 2] += bf_lo(hr[2 * i + 1]); acc[4 * i + 3] += bf_hi(hr[2 * i + 1]);
    }
    pin(acc);
    mbar_wait(bars + 8 * (B_RED + hf), 0);
    if (tid == 0) TSTAMP(60 + hf);
    float4 r[8];
#pragma unroll
    for (int i = 0; i < 8; i++) r[i] = *(const float4*)(smem + land + i * 2048);
    __syncwarp();
    const uint32_t ob = sb + land - lane * 16;
#pragma unroll
    for (int i = 0; i < 8; i += 2)
      stsm4(ob + (lane & 12) * 512 + (lane & 3) * 128 + (((i + (lane >> 4)) ^ (lane & 7)) << 4),
            pack_bf16(acc[4 * i] + r[i].x, acc[4 * i + 1] + r[i].y), pack_bf16(acc[4 * i + 2] + r[i].z, acc[4 * i + 3] + r[i].w),
            pack_bf16(acc[4 * i + 4] + r[i + 1].x, acc[4 * i + 5] + r[i + 1].y), pack_bf16(acc[4 * i + 6] + r[i + 1].z, acc[4 * i + 7] + r[i + 1].w));
    __syncwarp();
    uint4* op = (uint4*)(P.out + (size_t)(row0 - g8 + (lane >> 3)) * D_ + 64 * j) + (lane & 7);
#pragma unroll
    for (int i = 0; i < 4; i++) {
      uint4 v;
      asm volatile("ld.shared.v4.u32 {%0,%1,%2,%3}, [%4];" : "=r"(v.x), "=r"(v.y), "=r"(v.z), "=r"(v.w)
                   : "r"(ob + i * 2048 + (lane >> 3) * 128 + (((lane & 7) ^ ((4 * i + (lane >> 3)) & 7)) << 4)) : "memory");
      op[i * 256] = v;
    }
    if (tid == 0) TSTAMP(12 + hf * 8);
  }
}

__device__ __forceinline__ void ring_producer(uint32_t sb, int slot) {
  const int cta = fresh_cta(), g = cta >> 3, j = cta & 7, lane = fresh_tid() & 31;
  const uint32_t bars = sb + OFF_BAR, e1 = lds32(sb + OFF_SC + 4 * SC_EPOCH) + 1;
  const uint8_t* act = g_act + (size_t)g * G_STRIDE;
#pragma unroll 1
  for (int r = 6 + slot; r < 46; r += 6) {
    int hf, off, line, word, own;
    uint32_t bytes = 8 * KB, target = 4 * e1;
    if (r < 12) { hf = 1; word = r - 6 + (r - 6 >= j); off = G_O + 65536 + word * 8 * KB; line = C_OB + g; own = B_ADONE; target = 16 * e1; }
    else if (r < 28) { hf = r >= 20; word = (r - 12) & 7; off = G_H + (r - 12) * 8 * KB; line = C_H + 2 * g + hf; own = B_SA + hf; }
    else {
      hf = r >= 37;
      const int p = r - 26 - 9 * hf, i = k2_chunk(j, p);
      word = 2 * min((4 * i + (p < 5 ? 3 : 3 * (lane & 1))) / 11, 3) + (j & 1);
      off = G_HH + (hf * 172 + (j & 1) * 86 + 8 * i) * KB; line = C_HH + 2 * g + hf; own = (p < 5 ? B_S1 : B_SH) + hf;
      if (p < 5) word += 8;
      if (i == 10) bytes = 6 * KB;
    }
    const uint32_t fb = bars + 8 * (B_RF + 6 * hf + slot);
    mbar_wait(bars + 8 * own, 0);
    flag_wait(line, target, word);
    if (r >= 11) mbar_wait(bars + 8 * (r == 11 ? B_OWN : B_RE + slot), r < 12 ? 0 : (r / 6) & 1);
    if (elect_one()) {
      mbar_expect(fb, bytes);
      bulk_g2s(sb + (r < 12 ? 120 * KB : OFF_RING) + slot * 8 * KB, act + off, bytes, fb);
    }
  }
}

__device__ __forceinline__ void ln2_stats(uint8_t* smem, uint32_t sb) {
  const int g = fresh_cta() >> 3, lane = fresh_tid() & 31;
  const uint32_t bars = sb + OFF_BAR, epoch = lds32(sb + OFF_SC + 4 * SC_EPOCH);
  {
    const int u = (fresh_cta() & 7) == 7 ? 6 : 7;
    mbar_wait(bars + 8 * B_ADONE, 0);
    flag_wait(C_OB + g, (epoch + 1) * 16, u);
    mbar_wait(bars + 8 * B_OWN, 0);
    if (elect_one()) {
      mbar_expect(bars + 8 * B_OX, 8 * KB);
      bulk_g2s(sb + 44 * KB, g_act + (size_t)g * G_STRIDE + G_O + 65536 + u * 8 * KB, 8 * KB, bars + 8 * B_OX);
    }
  }
#pragma unroll 1
  for (int hf = 0; hf < 2; hf++) {
    mbar_wait(bars + 8 * (B_RF + 6 * hf + 5), hf);
    const float4* sp = (const float4*)(g_act + (size_t)g * G_STRIDE + G_ST + hf * 4096) + lane;
    float4 a;
#pragma unroll 1
    for (int n = 0; n < 100000; n++) {
      uint32_t m = 0;
      a = make_float4(0.f, 0.f, 0.f, 0.f);
#pragma unroll
      for (int i = 0; i < 8; i++) {
        float4 v;
        asm volatile("ld.relaxed.gpu.global.v4.f32 {%0,%1,%2,%3}, [%4];" : "=f"(v.x), "=f"(v.y), "=f"(v.z), "=f"(v.w) : "l"(sp + 32 * i) : "memory");
        a.x += v.x; a.y += v.y; a.z += v.z; a.w += v.w;
        m = max(m, __float_as_uint(v.y));
      }
      if (!__any_sync(~0u, m == 0xFFFFFFFFu)) break;
    }
    const float mean0 = a.x * (1.0f / D_), hr0 = 0.5f * rsqrtf(fmaxf(a.y * (1.0f / D_) - mean0 * mean0, 0.f) + LN_EPS);
    const float mean1 = a.z * (1.0f / D_), hr1 = 0.5f * rsqrtf(fmaxf(a.w * (1.0f / D_) - mean1 * mean1, 0.f) + LN_EPS);
    *(float4*)(smem + OFF_ST2 + hf * 512 + lane * 16) = make_float4(hr0, -mean0 * hr0, hr1, -mean1 * hr1);
    __syncwarp();
    if (lane == 0) mbar_arrive(bars + 8 * (B_ST2 + hf));
  }
}

__device__ __forceinline__ void weight_producer(const Params& P, uint32_t sb) {
  const int j = fresh_cta() & 7;
  const uint32_t bars = sb + OFF_BAR;
  if (elect_one()) {
    mbar_arrive(bars + 8 * (B_W1F + 1));
    fence_async_all();
#pragma unroll 1
    for (int k = 2; k < 8; k++) {
      mbar_wait2(bars + 8 * B_PDONE, 0, bars + 8 * (B_W1F + k - 2));
      if (k == 2) TSTAMP(15);
      mbar_expect(bars + 8 * (B_W1F + k), k == 2 ? 22 * KB + 704 : 22 * KB);
      if (k == 2) bulk_g2s(sb + OFF_CS, g_cs1 + f_start(j), 704, bars + 8 * (B_W1F + 2));
      load_w1(sb, j, k);
    }
    const int n0 = j * 64, k0 = (j & 1) * 688;
#pragma unroll 1
    for (int i = 0; i < 11; i++) {
      mbar_wait2(bars + 8 * (B_SW + (int)((W2_DEP >> (4 * i)) & 15)), 0, bars + 8 * (B_W2F + i - 2));
      const int kc = k0 + 64 * k2_chunk(j, i);
      mbar_expect(bars + 8 * (B_W2F + i), 16 * KB);
      tma2d(sb + ((uint32_t)(W2_A0 >> (5 * i)) & 31) * 8 * KB, &P.tw2, n0, kc, bars + 8 * (B_W2F + i));
      tma2d(sb + ((uint32_t)(W2_A1 >> (5 * i)) & 31) * 8 * KB, &P.tw2, n0 ^ 64, kc, bars + 8 * (B_W2F + i));
    }
  }
}

__global__ void __cluster_dims__(2, 1, 1) __launch_bounds__(512, 1) fused_block_kernel(const __grid_constant__ Params P) {
  extern __shared__ __align__(1024) uint8_t smem[];
  if (blockIdx.x >= NMAIN) { aux_cta(P, smem); return; }
  const uint32_t sb = s2u(smem), bars = sb + OFF_BAR;
  bool fast;
  {
    const int tid = threadIdx.x, lane = tid & 31;
    const int wid = __shfl_sync(~0u, tid >> 5, 0), wg = wid >> 2;
    const int bid = blockIdx.x, g = bid >> 3, j = bid & 7;
    uint32_t* sc = (uint32_t*)(smem + OFF_SC);
    float qacc[32];
    const uint32_t qdst = sb + OFF_Q + wg * 8192 + stsm_off(tid);
    if (wg < 2) {
      if (tid == 0) TSTAMP(0);
      if (wid == 1) {
        const bool el = elect_one();
        if (el) {
          mbar_init(bars + 8 * B_WKV, 1);
          mbar_expect(bars + 8 * B_WKV, 32 * KB);
          bulk_g2s(sb + OFF_WKV, P.wk, 16 * KB, bars + 8 * B_WKV);
          bulk_g2s(sb + OFF_WKV + 16 * KB, P.wv, 16 * KB, bars + 8 * B_WKV);
#pragma unroll
          for (int k = 0; k < 8; k++) mbar_init(bars + 8 * (B_XQ + k), 1);
        }
        __syncwarp();
        asm volatile("bar.arrive 12, 288;" ::: "memory");
        { const long long t0 = clock64(); while (clock64() - t0 < 1400) {} }
        if (elect_one()) {
#pragma unroll 1
          for (int k = 0; k < 8; k++) {
            mbar_expect(bars + 8 * (B_XQ + k), 24 * KB);
            tma2d(sb + OFF_X + 16 * KB * k, &P.tx, 64 * k, 128 * g, bars + 8 * (B_XQ + k));
            tma2d(sb + OFF_WQ + 8 * KB * k, &P.twq, 64 * j, 64 * k, bars + 8 * (B_XQ + k));
          }
        }
      } else {
        if (wid >= 3 && wid < 7 && elect_one()) asm volatile("prefetch.tensormap [%0];" ::"l"(&P.tx + (wid - 3)) : "memory");
        if (wid == 0) {
          float cs[8];
#pragma unroll
          for (int i = 0; i < 8; i++) cs[i] = 0.f;
          const uint4* wp = (const uint4*)(P.wq + (32 * (bid & 15) + (lane >> 3)) * D_ + 64 * (bid >> 4)) + (lane & 7);
#pragma unroll
          for (int h = 0; h < 8; h++) {
            const uint4 v = __ldg(wp + h * 256);
            cs[0] += bf_lo(v.x); cs[1] += bf_hi(v.x); cs[2] += bf_lo(v.y); cs[3] += bf_hi(v.y);
            cs[4] += bf_lo(v.z); cs[5] += bf_hi(v.z); cs[6] += bf_lo(v.w); cs[7] += bf_hi(v.w);
          }
#pragma unroll
          for (int i = 0; i < 8; i++) { cs[i] += __shfl_xor_sync(~0u, cs[i], 8); cs[i] += __shfl_xor_sync(~0u, cs[i], 16); }
          if (lane < 8) {
            *(float4*)(g_kv + (R_CS + 2 * lane) * 2048 + bid * 16) = make_float4(cs[0], cs[1], cs[2], cs[3]);
            *(float4*)(g_kv + (R_CS + 2 * lane + 1) * 2048 + bid * 16) = make_float4(cs[4], cs[5], cs[6], cs[7]);
          }
        }
        if (wid == 2 && elect_one()) {
          const uint32_t done = *(volatile unsigned int*)&g_cnt[C_DONE * CNT_STRIDE];
#pragma unroll
          for (int i = B_KV0; i < B_NUM; i++)
            mbar_init(bars + 8 * i, i < B_WO ? 1 : i < B_RE ? 2 : i < B_W1E ? 4 : i < B_ADONE ? 8 : 16);
#pragma unroll
          for (int i = 1; i < 7; i++) sc[i] = 0;
          sc[SC_EPOCH] = done / NCTA;
          asm volatile("fence.mbarrier_init.release.cluster;" ::: "memory");
        }
        __syncwarp();
        if (wid == 0 || wid == 2) asm volatile("bar.arrive 7, 320;" ::: "memory");
      }
      undef(qacc);
      const bool lead = elect_one();
      bar_sync(6, 512);
#pragma unroll 1
      for (int k = 0; k < 8; k++) {
        mbar_wait(bars + 8 * (B_XQ + k), 0);
        const uint64_t da = mkdesc(sb + OFF_X + wg * 8 * KB, 16, 1024, 1) + 1024 * k, db = mkdesc(sb + OFF_WQ, 8192, 1024, 1) + 512 * k;
        wg_fence();
#pragma unroll
        for (int s = 0; s < 4; s++) wgmma_n64_bt(qacc, da + 2 * s, db + 128 * s, s ? 1 : k);
        wg_commit();
        wg_wait<1>();
        if (k == 4 && lead) mbar_arrive(bars + 8 * B_X01);
      }
      wg_wait<0>();
      pin(qacc);
      if (lead) mbar_arrive(bars + 8 * B_XALL);
      if (tid == 0) TSTAMP(1);
      mbar_wait(bars + 8 * B_QS, 0);
      mbar_wait(bars + 8 * B_XALL, 0);
      const float2* sp = (const float2*)(smem + OFF_ST1) + wid * 16 + (lane >> 2);
      const float2 st0 = sp[0], st1 = sp[8];
      const float2* cs = (const float2*)(smem + OFF_CSQ) + (lane & 3);
      const float r0 = st0.y * QK_SCALE_LOG2, r1 = st1.y * QK_SCALE_LOG2, m0 = -st0.x * r0, m1 = -st1.x * r1;
      uint32_t nmax = 0;
#pragma unroll
      for (int h = 0; h < 4; h++) {
        uint32_t qh[4];
#pragma unroll
        for (int b = 2 * h; b < 2 * h + 2; b++) {
          const float2 cc = cs[4 * b];
          qacc[4 * b] = fmaf(qacc[4 * b], r0, m0 * cc.x); qacc[4 * b + 1] = fmaf(qacc[4 * b + 1], r0, m0 * cc.y);
          qacc[4 * b + 2] = fmaf(qacc[4 * b + 2], r1, m1 * cc.x); qacc[4 * b + 3] = fmaf(qacc[4 * b + 3], r1, m1 * cc.y);
          qh[2 * (b & 1)] = pack_f16(qacc[4 * b], qacc[4 * b + 1]);
          qh[2 * (b & 1) + 1] = pack_f16(qacc[4 * b + 2], qacc[4 * b + 3]);
        }
        stsm4(qdst + h * 2048, qh[0], qh[1], qh[2], qh[3]);
        float u[4], v[4];
        mma16816h(u, qh[0], qh[1], qh[2], qh[3], qh[0], qh[2]);
        mma16816h(v, qh[0], qh[1], qh[2], qh[3], qh[1], qh[3]);
        nmax = max(max(nmax, __float_as_uint(fabsf(u[0]))), __float_as_uint(fabsf(u[1])));
        nmax = max(max(nmax, __float_as_uint(fabsf(v[2]))), __float_as_uint(fabsf(v[3])));
      }
      nmax = __reduce_max_sync(~0u, nmax);
      if (lane == 0) atomicMax(&sc[SC_QMAX], nmax);
    } else {
      uint4 xr[4];
      const __nv_bfloat16* xp = P.x + (size_t)(bid * 16 + (lane >> 2)) * D_ + 64 * (wid - 8) + 8 * (lane & 3);
      xr[0] = __ldg((const uint4*)xp); xr[1] = __ldg((const uint4*)(xp + 8 * D_));
      xr[2] = __ldg((const uint4*)(xp + 32)); xr[3] = __ldg((const uint4*)(xp + 8 * D_ + 32));
      kv_path(smem, sb, xr);
      asm volatile("bar.arrive 6, 512;" ::: "memory");
      if (wid == 8) {
        if (elect_one()) {
          TSTAMP(27);
          flag_add(C_KV);
          TSTAMP(2);
        }
      } else if (wid < 12) {
        mbar_wait(bars + 8 * B_XALL, 0);
#pragma unroll 5
        for (int e = tid - 288; e < 1408; e += 96) *(uint4*)(smem + OFF_FILL + e * 16) = make_uint4(~0u, ~0u, ~0u, ~0u);
      } else {
        if (wid == 15) flag_wait(C_KV, (sc[SC_EPOCH] + 1) * NMAIN);
        bar_sync(5, 128);
        if (wid == 15) {
          if (elect_one()) {
            TSTAMP(3);
            mbar_wait(bars + 8 * B_X01, 0);
            mbar_expect(bars + 8 * B_KV0, 3 * CHB);
#pragma unroll 1
            for (int c = 0; c < 3; c++) bulk_g2s(sb + c * CHB, g_kv + c * CHB, CHB, bars + 8 * B_KV0);
            mbar_wait(bars + 8 * B_XALL, 0);
            mbar_wait(bars + 8 * B_QS, 0);
            mbar_expect(bars + 8 * B_KV1, 5 * CHB);
#pragma unroll 1
            for (int c = 3; c < 8; c++) bulk_g2s(sb + c * CHB, g_kv + c * CHB, CHB, bars + 8 * B_KV1);
          }
        } else if (wid == 14) {
          uint32_t km = 0, vm = 0;
#pragma unroll
          for (int i = 0; i < 4; i++) {
            const float4 a = __ldcg((const float4*)(g_kv + R_MX * 2048) + lane + 32 * i), b = __ldcg((const float4*)(g_kv + R_MX * 2048) + 128 + lane + 32 * i);
            km = max(km, __float_as_uint(a.x + a.y + a.z + a.w)); vm = max(vm, __float_as_uint(b.x + b.y + b.z + b.w));
          }
          km = __reduce_max_sync(~0u, km); vm = __reduce_max_sync(~0u, vm);
          if (lane == 0) { sc[SC_KMAX] = km; sc[SC_VMAX] = vm; }
        } else {
          if (wid == 13) {
            const float4* cp = (const float4*)(g_kv + (R_CS + (lane >> 1)) * 2048) + j * 16 + (lane & 1);
            float4 acc = __ldcg(cp);
#pragma unroll
            for (int i = 1; i < 8; i++) { const float4 v = __ldcg(cp + 2 * i); acc.x += v.x; acc.y += v.y; acc.z += v.z; acc.w += v.w; }
            acc.x += __shfl_xor_sync(~0u, acc.x, 1); acc.y += __shfl_xor_sync(~0u, acc.y, 1);
            acc.z += __shfl_xor_sync(~0u, acc.z, 1); acc.w += __shfl_xor_sync(~0u, acc.w, 1);
            if (lane & 1) *(float4*)(smem + OFF_CSQ + (lane >> 1) * 16) = acc;
          } else {
            const float4* sp = (const float4*)(g_kv + (R_ST + (lane >> 3)) * 2048) + g * 8 + (lane & 7);
            const float4 u = __ldcg(sp), v = __ldcg(sp + 512);
            *(float4*)(smem + OFF_ST1 + (lane & 7) * 128 + (lane >> 3) * 16) = u;
            *(float4*)(smem + OFF_ST1 + (lane & 7) * 128 + (lane >> 3) * 16 + 64) = v;
          }
          __syncwarp();
          if (lane == 0) mbar_arrive(bars + 8 * B_QS);
          if (tid == 416) TSTAMP(26);
        }
      }
      __syncwarp();
    }
    fence_async_smem();
    __syncthreads();
    const float q2 = __uint_as_float(sc[SC_QMAX]), k2 = __uint_as_float(sc[SC_KMAX]), v2 = __uint_as_float(sc[SC_VMAX]);
    fast = __all_sync(~0u, (q2 * k2 <= 56.f * 56.f) && (q2 <= 1048576.f) && (k2 <= 1048576.f) && (v2 <= 1e24f));
    if (tid == 0) TSTAMP(4);
    if (!fast) {
      mbar_wait(bars + 8 * B_KV0, 0);
      mbar_wait(bars + 8 * B_KV1, 0);
      if (wg < 2) {
#pragma unroll
        for (int h = 0; h < 4; h++) {
          constexpr float u = 1.0f / QK_SCALE_LOG2;
          stsm4(qdst + h * 2048, pack_bf16(qacc[8 * h] * u, qacc[8 * h + 1] * u), pack_bf16(qacc[8 * h + 2] * u, qacc[8 * h + 3] * u),
                pack_bf16(qacc[8 * h + 4] * u, qacc[8 * h + 5] * u), pack_bf16(qacc[8 * h + 6] * u, qacc[8 * h + 7] * u));
        }
      }
      for (int e = tid; e < 4096; e += 512) *(uint4*)(smem + (e >> 9) * CHB + (e & 511) * 16) = __ldcg((const uint4*)(g_kv + R_KP * 2048) + e);
      fence_async_smem();
      __syncthreads();
    }
  }
  {
    const int wq = __shfl_sync(~0u, fresh_tid() >> 5, 0), wg = wq >> 2;
    if (fast) attention_fast(P, sb, wg, (wq == 5) + 2 * (wq == 13), (wq & 3) == 3);
    else attention_safe(P, sb, wg, (wq == 5) + 2 * (wq == 13), (wq & 3) == 3);
  }
  const int wid = __shfl_sync(~0u, fresh_tid() >> 5, 0);
  if (fresh_tid() == 0) TSTAMP(5);
  if ((wid & 4) == 0) {
    post_chain(P, smem, sb, wid < 4);
    if (fresh_tid() == 0) { asm volatile("red.relaxed.gpu.global.add.u32 [%0], 1;" ::"l"(&g_cnt[C_DONE * CNT_STRIDE]) : "memory"); TSTAMP(6); }
  } else {
    if (wid == 15) weight_producer(P, sb);
    else if (wid == 7) ln2_stats(smem, sb);
    else ring_producer(sb, wid >= 8 ? wid & 3 : wid - 1);
  }
}

typedef CUresult (*EncodeFn)(CUtensorMap*, CUtensorMapDataType, cuuint32_t, void*, const cuuint64_t*, const cuuint64_t*, const cuuint32_t*,
                             const cuuint32_t*, CUtensorMapInterleave, CUtensorMapSwizzle, CUtensorMapL2promotion, CUtensorMapFloatOOBfill);

void make_map(EncodeFn enc, CUtensorMap* m, const void* ptr, int rows, int cols, int box_rows) {
  cuuint64_t dims[2] = {(cuuint64_t)cols, (cuuint64_t)rows}, strides[1] = {(cuuint64_t)cols * 2};
  cuuint32_t box[2] = {64, (cuuint32_t)box_rows}, es[2] = {1, 1};
  enc(m, CU_TENSOR_MAP_DATA_TYPE_BFLOAT16, 2, (void*)ptr, dims, strides, box, es, CU_TENSOR_MAP_INTERLEAVE_NONE,
      CU_TENSOR_MAP_SWIZZLE_128B, CU_TENSOR_MAP_L2_PROMOTION_L2_128B, CU_TENSOR_MAP_FLOAT_OOB_FILL_NONE);
}

}

extern "C" void kernel_launch(void* const* d_in, const int* in_sizes, int n_in, void* d_out, int out_size) {
  (void)in_sizes; (void)n_in; (void)out_size;
  static EncodeFn enc = nullptr;
  if (!enc) {
    cudaDriverEntryPointQueryResult qr;
    void* fn = nullptr;
    cudaGetDriverEntryPoint("cuTensorMapEncodeTiled", &fn, cudaEnableDefault, &qr);
    enc = (EncodeFn)fn;
    cudaFuncSetAttribute(fused_block_kernel, cudaFuncAttributeMaxDynamicSharedMemorySize, SMEM_BYTES);
  }
  Params P;
  const __nv_bfloat16* x = (const __nv_bfloat16*)d_in[0];
  make_map(enc, &P.tx, x, S_, D_, 128);
  make_map(enc, &P.twq, d_in[1], D_, D_, 64);
  make_map(enc, &P.two, d_in[4], D_, D_, 256);
  make_map(enc, &P.tw2, d_in[7], F_, D_, 64);
  P.x = x; P.wq = (const __nv_bfloat16*)d_in[1]; P.wk = (const __nv_bfloat16*)d_in[2]; P.wv = (const __nv_bfloat16*)d_in[3];
  P.wo = (const __nv_bfloat16*)d_in[4]; P.w1 = (const __nv_bfloat16*)d_in[6]; P.w2 = (const __nv_bfloat16*)d_in[7];
  P.out = (__nv_bfloat16*)d_out;
  P.c1 = 0xBF00BF00u; P.c2 = 0x00030003u; P.c3 = 0x9F809F80u;
  fused_block_kernel<<<NCTA, 512, SMEM_BYTES>>>(P);
}
```

```cpp
#include <cuda_runtime.h>
#include <cuda_bf16.h>
#include <cuda_fp16.h>
#include <cuda.h>
#include <stdint.h>

#define FORCE_REDO 0
namespace {

constexpr int S_ = 2048, D_ = 512, F_ = 1376;
constexpr int NMAIN = 128, NAUX = 4, NCTA = NMAIN + NAUX;
constexpr float LN_EPS = 1e-5f;
constexpr float QK_SCALE_LOG2 = 0.25f * 1.4426950408889634f;

constexpr int KV_ROWS = 138, R_KP = 80, R_ST = 112, R_MX = 120, R_CS = 122;
__device__ __align__(1024) uint8_t g_kv[KV_ROWS * 2048];
constexpr int G_O = 0, G_H = 131072, G_HH = 262144, G_ST = G_HH + 344 * 1024, G_STRIDE = G_ST + 8192;
__device__ __align__(1024) uint8_t g_act[16 * G_STRIDE];
__device__ __align__(16) uint4 g_cs1[176 * 3];
__device__ __align__(1024) uint8_t g_w1t[8 * 176 * 1024];
constexpr int CNT_STRIDE = 32;
enum { C_KV = 0, C_AUX = 1, C_DONE = 2, C_O = 4, C_OB = C_O + 16, C_H = C_OB + 16, C_HH = C_H + 32, C_NUM = C_HH + 32 };
__device__ unsigned int g_cnt[C_NUM * CNT_STRIDE];
#define TSTAMP(i) do {} while (0)
#define LSTAMP(c, i) do {} while (0)

constexpr int KB = 1024;
constexpr int CHB = 20 * KB;
constexpr int OFF_Q = 160 * KB;
constexpr int OFF_X = 0;
constexpr int OFF_WQ = 128 * KB;
constexpr int OFF_WKV = 192 * KB;
constexpr int OFF_WO = 56 * KB;
constexpr int OFF_RING = 176 * KB;
constexpr int OFF_FILL = 200 * KB;
constexpr int OFF_MISC = 224 * KB;
constexpr int OFF_KVS = OFF_MISC;
constexpr int OFF_CS = OFF_KVS;
constexpr int OFF_ST2 = OFF_KVS + 1152;
constexpr int OFF_FL = OFF_KVS + 2176;
constexpr int OFF_BAR = OFF_KVS + 2208;
constexpr int OFF_SC = OFF_BAR + 656;
constexpr int OFF_CSQ = OFF_WKV, OFF_ST1 = OFF_WKV + 256;
constexpr int SMEM_BYTES = OFF_MISC + 3072;
enum { B_XQ = 0  , B_WKV = 8,
       B_KV0 = 9, B_KV1 = 10, B_W1F = 11  , B_W2F = 19  , B_RF = 30  , B_RED = 42  , B_OX = 44, B_ST2 = 45  ,
       B_WO = 47, B_QS = 48,
       B_RE = 49  , B_OWN = 55, B_SA = 56  , B_S1 = 58  , B_SH = 60  , B_SW = 62  ,
       B_W1E = 64  , B_LAND = 72, B_PDONE = 73, B_X01 = 74, B_XALL = 75,
       B_ADONE = 76, B_F2 = 77, B_OA = 78, B_NUM = 79 };
enum { SC_EPOCH = 0, SC_QMAX = 1, SC_KMAX = 2, SC_VMAX = 3, SC_FREE = 4   };
constexpr uint64_t W1_SLOT = 0x54327610u;
constexpr uint64_t W2_A0 = 0x380d129062ce23ull, W2_A1 = 0x3c3062d27ad244ull;
constexpr uint64_t W2_DEP = 0x10988766543ull;

__device__ __forceinline__ uint32_t s2u(const void* p) { return (uint32_t)__cvta_generic_to_shared(p); }
__device__ __forceinline__ void mbar_init(uint32_t b, int c) { asm volatile("mbarrier.init.shared::cta.b64 [%0], %1;" ::"r"(b), "r"(c) : "memory"); }
__device__ __forceinline__ void mbar_expect(uint32_t b, uint32_t n) { asm volatile("mbarrier.arrive.expect_tx.shared::cta.b64 _, [%0], %1;" ::"r"(b), "r"(n) : "memory"); }
__device__ __forceinline__ void mbar_arrive(uint32_t b) { asm volatile("mbarrier.arrive.shared::cta.b64 _, [%0];" ::"r"(b) : "memory"); }
__device__ __forceinline__ void mbar_wait(uint32_t b, uint32_t ph) {
  asm volatile("{\n.reg .pred p;\n.reg .u32 n;\nmov.u32 n, 0;\n"
               "W%=:\nmbarrier.try_wait.parity.shared::cta.b64 p, [%0], %1;\n@p bra D%=;\n"
               "add.u32 n, n, 1;\nsetp.lt.u32 p, n, 400000;\n@p bra W%=;\nD%=:\n}" ::"r"(b), "r"(ph) : "memory");
}
__device__ __forceinline__ void bulk_g2s(uint32_t dst, const void* src, uint32_t n, uint32_t bar) {
  asm volatile("cp.async.bulk.shared::cluster.global.mbarrier::complete_tx::bytes [%0], [%1], %2, [%3];" ::"r"(dst), "l"(src), "r"(n), "r"(bar) : "memory");
}
__device__ __forceinline__ void tma2d(uint32_t dst, const CUtensorMap* m, int c0, int c1, uint32_t bar) {
  asm volatile("cp.async.bulk.tensor.2d.shared::cluster.global.mbarrier::complete_tx::bytes [%0], [%1, {%3, %4}], [%2];"
               ::"r"(dst), "l"(m), "r"(bar), "r"(c0), "r"(c1) : "memory");
}
__device__ __forceinline__ void l2_prefetch(const void* p, uint32_t n) { asm volatile("cp.async.bulk.prefetch.L2.global [%0], %1;" ::"l"(p), "r"(n) : "memory"); }
__device__ __forceinline__ void fence_async_smem() { asm volatile("fence.proxy.async.shared::cta;" ::: "memory"); }
__device__ __forceinline__ void fence_async_all() { asm volatile("fence.proxy.async.global;" ::: "memory"); }
__device__ __forceinline__ void bar_sync(int id, int n) { asm volatile("bar.sync %0, %1;" ::"r"(id), "r"(n) : "memory"); }
__device__ __forceinline__ void flag_add(int c) { asm volatile("red.release.gpu.global.add.u32 [%0], 1;" ::"l"(&g_cnt[c * CNT_STRIDE]) : "memory"); }
__device__ __forceinline__ void hint_wait(int c, unsigned int target, int word) {
  unsigned int v; int n = 0;
  do { asm volatile("ld.relaxed.gpu.global.u32 %0, [%1];" : "=r"(v) : "l"(&g_cnt[c * CNT_STRIDE + word]) : "memory");
     } while ((int)(v - target) < 0 && ++n < 400000);
}
__device__ __forceinline__ void flag_wait(int c, unsigned int target) {
  hint_wait(c, target, 0);
  asm volatile("fence.acquire.gpu;" ::: "memory");
  fence_async_all();
}
__device__ __forceinline__ void mbar_wait2(uint32_t b0, uint32_t ph0, uint32_t b1) {
  asm volatile("{\n.reg .pred p, q;\n.reg .u32 n;\nmov.u32 n, 0;\n"
               "W%=:\nmbarrier.try_wait.parity.shared::cta.b64 p, [%0], %1;\nmbarrier.try_wait.parity.shared::cta.b64 q, [%2], 0;\n"
               "and.pred p, p, q;\n@p bra D%=;\n"
               "add.u32 n, n, 1;\nsetp.lt.u32 p, n, 400000;\n@p bra W%=;\nD%=:\n}" ::"r"(b0), "r"(ph0), "r"(b1) : "memory");
}
__device__ __forceinline__ bool elect_one() {
  uint32_t p;
  asm volatile("{\n.reg .pred P;\nelect.sync _|P, 0xffffffff;\nselp.u32 %0, 1, 0, P;\n}" : "=r"(p));
  return p != 0;
}
__device__ __forceinline__ int fresh_tid() { int t; asm volatile("mov.u32 %0, %%tid.x;" : "=r"(t)); return t; }
__device__ __forceinline__ int fresh_cta() { int t; asm volatile("mov.u32 %0, %%ctaid.x;" : "=r"(t)); return t; }
__device__ __forceinline__ uint32_t lds32(uint32_t a) { uint32_t v; asm volatile("ld.shared.u32 %0, [%1];" : "=r"(v) : "r"(a) : "memory"); return v; }
__device__ __forceinline__ void ldsm4t(uint32_t (&r)[4], uint32_t a) {
  asm volatile("ldmatrix.sync.aligned.m8n8.x4.trans.shared.b16 {%0,%1,%2,%3}, [%4];" : "=r"(r[0]), "=r"(r[1]), "=r"(r[2]), "=r"(r[3]) : "r"(a) : "memory");
}
__device__ __forceinline__ void hint_add(int flag, int word) {
  asm volatile("red.relaxed.gpu.global.add.u32 [%0], 1;" ::"l"(&g_cnt[flag * CNT_STRIDE + word]) : "memory");
}
__device__ __forceinline__ void stg32(void* p, uint32_t v) { asm volatile("st.global.u32 [%0], %1;" ::"l"(p), "r"(v) : "memory"); }
__device__ __forceinline__ void bulk_s2g(void* dst, uint32_t src, uint32_t n) {
  asm volatile("cp.async.bulk.global.shared::cta.bulk_group [%0], [%1], %2;" ::"l"(dst), "r"(src), "r"(n) : "memory");
}
__device__ __forceinline__ void stsm4(uint32_t a, uint32_t r0, uint32_t r1, uint32_t r2, uint32_t r3) {
  asm volatile("stmatrix.sync.aligned.m8n8.x4.shared.b16 [%0], {%1,%2,%3,%4};" ::"r"(a), "r"(r0), "r"(r1), "r"(r2), "r"(r3) : "memory");
}
__device__ __forceinline__ uint32_t stsm_off(int tid) { return (tid & 16) * 64 + (tid & 96) * 8 + (tid & 15) * 16; }
template <int N> __device__ __forceinline__ void undef(float (&d)[N]) {
#pragma unroll
  for (int i = 0; i < N; i++) asm volatile("" : "=f"(d[i]));
}
__device__ __forceinline__ void wg_fence() { asm volatile("wgmma.fence.sync.aligned;" ::: "memory"); }
__device__ __forceinline__ void wg_commit() { asm volatile("wgmma.commit_group.sync.aligned;" ::: "memory"); }
template <int N> __device__ __forceinline__ void wg_wait() { asm volatile("wgmma.wait_group.sync.aligned %0;" ::"n"(N) : "memory"); }
__device__ __forceinline__ uint64_t mkdesc(uint32_t addr, uint32_t lbo, uint32_t sbo, uint32_t swz = 0) {
  return (uint64_t)((addr & 0x3FFFF) >> 4) | ((uint64_t)(lbo >> 4) << 16) | ((uint64_t)(sbo >> 4) << 32) | ((uint64_t)swz << 62);
}
template <int N> __device__ __forceinline__ void pin(float (&d)[N]) {
#pragma unroll
  for (int i = 0; i < N; i++) asm volatile("" : "+f"(d[i])::"memory");
}
template <int N> __device__ __forceinline__ void pin(uint32_t (&d)[N]) {
#pragma unroll
  for (int i = 0; i < N; i++) asm volatile("" : "+r"(d[i])::"memory");
}
__device__ __forceinline__ uint32_t pack_bf16(float lo, float hi) { uint32_t r; asm("cvt.rn.bf16x2.f32 %0, %1, %2;" : "=r"(r) : "f"(hi), "f"(lo)); return r; }
__device__ __forceinline__ uint32_t pack_f16(float lo, float hi) { uint32_t r; asm("cvt.rn.f16x2.f32 %0, %1, %2;" : "=r"(r) : "f"(hi), "f"(lo)); return r; }
__device__ __forceinline__ float bf_lo(uint32_t u) { return __uint_as_float(u << 16); }
__device__ __forceinline__ float bf_hi(uint32_t u) { return __uint_as_float(u & 0xFFFF0000u); }
__device__ __forceinline__ uint32_t split_bf16(float v) { return pack_bf16(v, v - bf_lo(pack_bf16(v, 0.f))); }
template <int NB> __device__ __forceinline__ void redo_gemm(float (&acc)[4 * NB], const uint8_t* img, int kn, const __nv_bfloat16* w, int ldw, int flip, float sh0 = 0.f, float sh1 = 0.f) {
  if (!FORCE_REDO && !__any_sync(~0u, isnan(acc[0] + acc[2]))) return;
#pragma unroll
  for (int i = 0; i < 4 * NB; i++) acc[i] = 0.f;
#pragma unroll 1
  for (int k = 0; k < kn; k++) {
    uint32_t a0, a1;
    int n = 0;
    do {
      asm volatile("ld.relaxed.gpu.global.u32 %0, [%1];" : "=r"(a0) : "l"(img + (k >> 3) * 1024 + (k & 6) * 2) : "memory");
      asm volatile("ld.relaxed.gpu.global.u32 %0, [%1];" : "=r"(a1) : "l"(img + (k >> 3) * 1024 + (k & 6) * 2 + 128) : "memory");
    } while (max(a0, a1) == 0xFFFFFFFFu && ++n < 10000);
    const float x0 = ((k & 1) ? bf_hi(a0) : bf_lo(a0)) + sh0, x1 = ((k & 1) ? bf_hi(a1) : bf_lo(a1)) + sh1;
#pragma unroll
    for (int b = 0; b < NB; b++) {
      const uint32_t v = __ldg((const uint32_t*)(w + (size_t)k * ldw + (b < 8 ? 8 * b : 8 * b + flip)));
      acc[4 * b] = fmaf(x0, bf_lo(v), acc[4 * b]); acc[4 * b + 1] = fmaf(x0, bf_hi(v), acc[4 * b + 1]);
      acc[4 * b + 2] = fmaf(x1, bf_lo(v), acc[4 * b + 2]); acc[4 * b + 3] = fmaf(x1, bf_hi(v), acc[4 * b + 3]);
    }
  }
}
__device__ __forceinline__ float ex2(float x) { float r; asm("ex2.approx.ftz.f32 %0, %1;" : "=f"(r) : "f"(x)); return r; }
__device__ __forceinline__ void mma16816(float (&d)[4], uint32_t a0, uint32_t a1, uint32_t a2, uint32_t a3, uint32_t b0, uint32_t b1) {
  asm volatile("mma.sync.aligned.m16n8k16.row.col.f32.bf16.bf16.f32 {%0,%1,%2,%3},{%4,%5,%6,%7},{%8,%9},{%0,%1,%2,%3};"
               : "+f"(d[0]), "+f"(d[1]), "+f"(d[2]), "+f"(d[3]) : "r"(a0), "r"(a1), "r"(a2), "r"(a3), "r"(b0), "r"(b1));
}
__device__ __forceinline__ void mma16816h(float (&d)[4], uint32_t a0, uint32_t a1, uint32_t a2, uint32_t a3, uint32_t b0, uint32_t b1) {
  asm("mma.sync.aligned.m16n8k16.row.col.f32.f16.f16.f32 {%0,%1,%2,%3},{%4,%5,%6,%7},{%8,%9},{%10,%10,%10,%10};"
      : "=f"(d[0]), "=f"(d[1]), "=f"(d[2]), "=f"(d[3]) : "r"(a0), "r"(a1), "r"(a2), "r"(a3), "r"(b0), "r"(b1), "f"(0.f));
}
__device__ __forceinline__ void wgmma_n64_bt(float (&d)[32], uint64_t da, uint64_t db, int sd) {
  asm volatile("{.reg .pred p; setp.ne.b32 p, %34, 0;\n"
  "wgmma.mma_async.sync.aligned.m64n64k16.f32.bf16.bf16 {%0, %1, %2, %3, %4, %5, %6, %7, %8, %9, %10, %11, %12, %13, %14, %15, %16, %17, %18, %19, %20, %21, %22, %23, %24, %25, %26, %27, %28, %29, %30, %31}, %32, %33, p, 1, 1, 0, 1;}\n"
  : "+f"(d[0]), "+f"(d[1]), "+f"(d[2]), "+f"(d[3]), "+f"(d[4]), "+f"(d[5]), "+f"(d[6]), "+f"(d[7]), "+f"(d[8]), "+f"(d[9]), "+f"(d[10]), "+f"(d[11]), "+f"(d[12]), "+f"(d[13]), "+f"(d[14]), "+f"(d[15]), "+f"(d[16]), "+f"(d[17]), "+f"(d[18]), "+f"(d[19]), "+f"(d[20]), "+f"(d[21]), "+f"(d[22]), "+f"(d[23]), "+f"(d[24]), "+f"(d[25]), "+f"(d[26]), "+f"(d[27]), "+f"(d[28]), "+f"(d[29]), "+f"(d[30]), "+f"(d[31]) : "l"(da), "l"(db), "r"(sd));
}
__device__ __forceinline__ void wgmma_n128_bt(float (&d)[64], uint64_t da, uint64_t db, int sd) {
  asm volatile("{.reg .pred p; setp.ne.b32 p, %66, 0;\n"
  "wgmma.mma_async.sync.aligned.m64n128k16.f32.bf16.bf16 {%0, %1, %2, %3, %4, %5, %6, %7, %8, %9, %10, %11, %12, %13, %14, %15, %16, %17, %18, %19, %20, %21, %22, %23, %24, %25, %26, %27, %28, %29, %30, %31, %32, %33, %34, %35, %36, %37, %38, %39, %40, %41, %42, %43, %44, %45, %46, %47, %48, %49, %50, %51, %52, %53, %54, %55, %56, %57, %58, %59, %60, %61, %62, %63}, %64, %65, p, 1, 1, 0, 1;}\n"
  : "+f"(d[0]), "+f"(d[1]), "+f"(d[2]), "+f"(d[3]), "+f"(d[4]), "+f"(d[5]), "+f"(d[6]), "+f"(d[7]), "+f"(d[8]), "+f"(d[9]), "+f"(d[10]), "+f"(d[11]), "+f"(d[12]), "+f"(d[13]), "+f"(d[14]), "+f"(d[15]), "+f"(d[16]), "+f"(d[17]), "+f"(d[18]), "+f"(d[19]), "+f"(d[20]), "+f"(d[21]), "+f"(d[22]), "+f"(d[23]), "+f"(d[24]), "+f"(d[25]), "+f"(d[26]), "+f"(d[27]), "+f"(d[28]), "+f"(d[29]), "+f"(d[30]), "+f"(d[31]), "+f"(d[32]), "+f"(d[33]), "+f"(d[34]), "+f"(d[35]), "+f"(d[36]), "+f"(d[37]), "+f"(d[38]), "+f"(d[39]), "+f"(d[40]), "+f"(d[41]), "+f"(d[42]), "+f"(d[43]), "+f"(d[44]), "+f"(d[45]), "+f"(d[46]), "+f"(d[47]), "+f"(d[48]), "+f"(d[49]), "+f"(d[50]), "+f"(d[51]), "+f"(d[52]), "+f"(d[53]), "+f"(d[54]), "+f"(d[55]), "+f"(d[56]), "+f"(d[57]), "+f"(d[58]), "+f"(d[59]), "+f"(d[60]), "+f"(d[61]), "+f"(d[62]), "+f"(d[63]) : "l"(da), "l"(db), "r"(sd));
}
__device__ __forceinline__ void wgmma_n176_bt(float (&d)[88], uint64_t da, uint64_t db, int sd) {
  asm volatile("{.reg .pred p; setp.ne.b32 p, %90, 0;\n"
  "wgmma.mma_async.sync.aligned.m64n176k16.f32.bf16.bf16 {%0, %1, %2, %3, %4, %5, %6, %7, %8, %9, %10, %11, %12, %13, %14, %15, %16, %17, %18, %19, %20, %21, %22, %23, %24, %25, %26, %27, %28, %29, %30, %31, %32, %33, %34, %35, %36, %37, %38, %39, %40, %41, %42, %43, %44, %45, %46, %47, %48, %49, %50, %51, %52, %53, %54, %55, %56, %57, %58, %59, %60, %61, %62, %63, %64, %65, %66, %67, %68, %69, %70, %71, %72, %73, %74, %75, %76, %77, %78, %79, %80, %81, %82, %83, %84, %85, %86, %87}, %88, %89, p, 1, 1, 0, 1;}\n"
  : "+f"(d[0]), "+f"(d[1]), "+f"(d[2]), "+f"(d[3]), "+f"(d[4]), "+f"(d[5]), "+f"(d[6]), "+f"(d[7]), "+f"(d[8]), "+f"(d[9]), "+f"(d[10]), "+f"(d[11]), "+f"(d[12]), "+f"(d[13]), "+f"(d[14]), "+f"(d[15]), "+f"(d[16]), "+f"(d[17]), "+f"(d[18]), "+f"(d[19]), "+f"(d[20]), "+f"(d[21]), "+f"(d[22]), "+f"(d[23]), "+f"(d[24]), "+f"(d[25]), "+f"(d[26]), "+f"(d[27]), "+f"(d[28]), "+f"(d[29]), "+f"(d[30]), "+f"(d[31]), "+f"(d[32]), "+f"(d[33]), "+f"(d[34]), "+f"(d[35]), "+f"(d[36]), "+f"(d[37]), "+f"(d[38]), "+f"(d[39]), "+f"(d[40]), "+f"(d[41]), "+f"(d[42]), "+f"(d[43]), "+f"(d[44]), "+f"(d[45]), "+f"(d[46]), "+f"(d[47]), "+f"(d[48]), "+f"(d[49]), "+f"(d[50]), "+f"(d[51]), "+f"(d[52]), "+f"(d[53]), "+f"(d[54]), "+f"(d[55]), "+f"(d[56]), "+f"(d[57]), "+f"(d[58]), "+f"(d[59]), "+f"(d[60]), "+f"(d[61]), "+f"(d[62]), "+f"(d[63]), "+f"(d[64]), "+f"(d[65]), "+f"(d[66]), "+f"(d[67]), "+f"(d[68]), "+f"(d[69]), "+f"(d[70]), "+f"(d[71]), "+f"(d[72]), "+f"(d[73]), "+f"(d[74]), "+f"(d[75]), "+f"(d[76]), "+f"(d[77]), "+f"(d[78]), "+f"(d[79]), "+f"(d[80]), "+f"(d[81]), "+f"(d[82]), "+f"(d[83]), "+f"(d[84]), "+f"(d[85]), "+f"(d[86]), "+f"(d[87]) : "l"(da), "l"(db), "r"(sd));
}
__device__ __forceinline__ void wgmma_qk_f16(float (&d)[32], uint64_t da, uint64_t db, int sd) {
  asm volatile("{.reg .pred p; setp.ne.b32 p, %34, 0;\n"
  "wgmma.mma_async.sync.aligned.m64n64k16.f32.f16.f16 {%0, %1, %2, %3, %4, %5, %6, %7, %8, %9, %10, %11, %12, %13, %14, %15, %16, %17, %18, %19, %20, %21, %22, %23, %24, %25, %26, %27, %28, %29, %30, %31}, %32, %33, p, 1, 1, 0, 0;}\n"
  : "+f"(d[0]), "+f"(d[1]), "+f"(d[2]), "+f"(d[3]), "+f"(d[4]), "+f"(d[5]), "+f"(d[6]), "+f"(d[7]), "+f"(d[8]), "+f"(d[9]), "+f"(d[10]), "+f"(d[11]), "+f"(d[12]), "+f"(d[13]), "+f"(d[14]), "+f"(d[15]), "+f"(d[16]), "+f"(d[17]), "+f"(d[18]), "+f"(d[19]), "+f"(d[20]), "+f"(d[21]), "+f"(d[22]), "+f"(d[23]), "+f"(d[24]), "+f"(d[25]), "+f"(d[26]), "+f"(d[27]), "+f"(d[28]), "+f"(d[29]), "+f"(d[30]), "+f"(d[31]) : "l"(da), "l"(db), "r"(sd));
}
__device__ __forceinline__ void wgmma_qk_bf16(float (&d)[32], uint64_t da, uint64_t db, int sd) {
  asm volatile("{.reg .pred p; setp.ne.b32 p, %34, 0;\n"
  "wgmma.mma_async.sync.aligned.m64n64k16.f32.bf16.bf16 {%0, %1, %2, %3, %4, %5, %6, %7, %8, %9, %10, %11, %12, %13, %14, %15, %16, %17, %18, %19, %20, %21, %22, %23, %24, %25, %26, %27, %28, %29, %30, %31}, %32, %33, p, 1, 1, 0, 0;}\n"
  : "+f"(d[0]), "+f"(d[1]), "+f"(d[2]), "+f"(d[3]), "+f"(d[4]), "+f"(d[5]), "+f"(d[6]), "+f"(d[7]), "+f"(d[8]), "+f"(d[9]), "+f"(d[10]), "+f"(d[11]), "+f"(d[12]), "+f"(d[13]), "+f"(d[14]), "+f"(d[15]), "+f"(d[16]), "+f"(d[17]), "+f"(d[18]), "+f"(d[19]), "+f"(d[20]), "+f"(d[21]), "+f"(d[22]), "+f"(d[23]), "+f"(d[24]), "+f"(d[25]), "+f"(d[26]), "+f"(d[27]), "+f"(d[28]), "+f"(d[29]), "+f"(d[30]), "+f"(d[31]) : "l"(da), "l"(db), "r"(sd));
}
__device__ __forceinline__ void wgmma_pv(float (&d)[12], uint32_t a0, uint32_t a1, uint32_t a2, uint32_t a3, uint64_t db) {
  asm volatile("wgmma.mma_async.sync.aligned.m64n24k16.f32.bf16.bf16 {%0, %1, %2, %3, %4, %5, %6, %7, %8, %9, %10, %11}, {%12, %13, %14, %15}, %16, 1, 1, 1, 1;\n"
  : "+f"(d[0]), "+f"(d[1]), "+f"(d[2]), "+f"(d[3]), "+f"(d[4]), "+f"(d[5]), "+f"(d[6]), "+f"(d[7]), "+f"(d[8]), "+f"(d[9]), "+f"(d[10]), "+f"(d[11]) : "r"(a0), "r"(a1), "r"(a2), "r"(a3), "l"(db));
}
__device__ __forceinline__ void wgmma_r176(float (&d)[88], uint32_t a0, uint32_t a1, uint32_t a2, uint32_t a3, uint64_t db) {
  asm volatile("wgmma.mma_async.sync.aligned.m64n176k16.f32.bf16.bf16 {%0, %1, %2, %3, %4, %5, %6, %7, %8, %9, %10, %11, %12, %13, %14, %15, %16, %17, %18, %19, %20, %21, %22, %23, %24, %25, %26, %27, %28, %29, %30, %31, %32, %33, %34, %35, %36, %37, %38, %39, %40, %41, %42, %43, %44, %45, %46, %47, %48, %49, %50, %51, %52, %53, %54, %55, %56, %57, %58, %59, %60, %61, %62, %63, %64, %65, %66, %67, %68, %69, %70, %71, %72, %73, %74, %75, %76, %77, %78, %79, %80, %81, %82, %83, %84, %85, %86, %87}, {%88, %89, %90, %91}, %92, 1, 1, 1, 1;\n"
  : "+f"(d[0]), "+f"(d[1]), "+f"(d[2]), "+f"(d[3]), "+f"(d[4]), "+f"(d[5]), "+f"(d[6]), "+f"(d[7]), "+f"(d[8]), "+f"(d[9]), "+f"(d[10]), "+f"(d[11]), "+f"(d[12]), "+f"(d[13]), "+f"(d[14]), "+f"(d[15]), "+f"(d[16]), "+f"(d[17]), "+f"(d[18]), "+f"(d[19]), "+f"(d[20]), "+f"(d[21]), "+f"(d[22]), "+f"(d[23]), "+f"(d[24]), "+f"(d[25]), "+f"(d[26]), "+f"(d[27]), "+f"(d[28]), "+f"(d[29]), "+f"(d[30]), "+f"(d[31]), "+f"(d[32]), "+f"(d[33]), "+f"(d[34]), "+f"(d[35]), "+f"(d[36]), "+f"(d[37]), "+f"(d[38]), "+f"(d[39]), "+f"(d[40]), "+f"(d[41]), "+f"(d[42]), "+f"(d[43]), "+f"(d[44]), "+f"(d[45]), "+f"(d[46]), "+f"(d[47]), "+f"(d[48]), "+f"(d[49]), "+f"(d[50]), "+f"(d[51]), "+f"(d[52]), "+f"(d[53]), "+f"(d[54]), "+f"(d[55]), "+f"(d[56]), "+f"(d[57]), "+f"(d[58]), "+f"(d[59]), "+f"(d[60]), "+f"(d[61]), "+f"(d[62]), "+f"(d[63]), "+f"(d[64]), "+f"(d[65]), "+f"(d[66]), "+f"(d[67]), "+f"(d[68]), "+f"(d[69]), "+f"(d[70]), "+f"(d[71]), "+f"(d[72]), "+f"(d[73]), "+f"(d[74]), "+f"(d[75]), "+f"(d[76]), "+f"(d[77]), "+f"(d[78]), "+f"(d[79]), "+f"(d[80]), "+f"(d[81]), "+f"(d[82]), "+f"(d[83]), "+f"(d[84]), "+f"(d[85]), "+f"(d[86]), "+f"(d[87]) : "r"(a0), "r"(a1), "r"(a2), "r"(a3), "l"(db));
}

__host__ __device__ constexpr char ptype(int i) { return "LLMMIILLMILLIIMM"[i]; }
constexpr float INIT_L = 256.0f + 127.0f - 77.164f / 128.0f + 1.0f / 256.0f;
constexpr float INIT_I = 256.0f + 190.0f - 75.041f / 128.0f + 1.0f / 256.0f;
__host__ __device__ constexpr float initv(int i) { return ptype(i) == 'M' ? 0.0f : ptype(i) == 'L' ? INIT_L : INIT_I; }
__device__ __forceinline__ uint32_t exp_pair(char ty, float a, float b, uint32_t c1, uint32_t c2, uint32_t c3) {
  if (ty == 'M') return pack_bf16(ex2(a), ex2(b));
  uint32_t y = __byte_perm(__float_as_uint(a), __float_as_uint(b), 0x6521), m, e, r;
  if (ty == 'L') {
    asm("lop3.b32 %0, %1, 0x007F007F, %2, 0xEA;" : "=r"(m) : "r"(y), "r"(c1));
    asm("lop3.b32 %0, %1, 0x7F807F80, %2, 0xEA;" : "=r"(e) : "r"(y), "r"(c2));
  } else {
    asm("lop3.b32 %0, %1, 0x007F007F, %2, 0xEA;" : "=r"(m) : "r"(y), "r"(c3));
    e = y - m;
  }
  asm("fma.rn.bf16x2 %0, %1, %2, %3;" : "=r"(r) : "r"(y), "r"(m), "r"(e));
  return r;
}
template <int HF> __device__ __forceinline__ void exp_half(const float (&s)[32], uint32_t (&p)[8], uint32_t c1, uint32_t c2, uint32_t c3) {
#pragma unroll
  for (int i = HF * 8; i < HF * 8 + 8; i++) p[i - HF * 8] = exp_pair(ptype(i), s[2 * i], s[2 * i + 1], c1, c2, c3);
}

struct Params {
  CUtensorMap tx, twq, two, tw2;
  const __nv_bfloat16 *x, *wq, *wk, *wv, *wo, *w1, *w2;
  __nv_bfloat16* out;
  uint32_t c1, c2, c3;
};

constexpr uint64_t RING_PAR = 0x620bdfc0000ull;
__device__ __forceinline__ int k2_chunk(int j, int p) {
  const uint64_t t = j < 4 ? (j < 2 ? 0xa9754286310ull : 0xa9752186043ull) : (j < 6 ? 0xa9542183076ull : 0xa7542163098ull);
  return (int)(t >> (4 * p)) & 15;
}
__device__ __forceinline__ int f_start(int j) { int n4 = j >> 1; return 688 * (j & 1) + (n4 == 3 ? 512 : 176 * n4); }

__device__ __forceinline__ void load_w1(uint32_t sb, int j, int k) {
  bulk_g2s(sb + (uint32_t)((W1_SLOT >> (4 * k)) & 7) * 22 * KB, g_w1t + (j * 8 + k) * 22 * KB, 22 * KB, sb + OFF_BAR + 8 * (B_W1F + k));
}

__device__ __forceinline__ void region_freed(const Params& P, uint32_t sb, int it, bool duty) {
  const uint32_t bars = sb + OFF_BAR;
  uint32_t old = 0;
  if (elect_one()) {
    if (duty) {
      const int g = fresh_cta() >> 3;
      if (it == 0) {
        mbar_wait(bars + 8 * B_OA, 0);
        flag_add(C_O + g);
      } else if (it == 1) {
        asm volatile("cp.async.cg.shared.global [%0], [%1], 16;" ::"r"(sb + OFF_FL), "l"(&g_cnt[(C_O + g) * CNT_STRIDE]) : "memory");
        asm volatile("cp.async.cg.shared.global [%0], [%1], 16;" ::"r"(sb + OFF_FL + 16), "l"(&g_cnt[C_AUX * CNT_STRIDE]) : "memory");
      } else {
        asm volatile("cp.async.wait_all;" ::: "memory");
        mbar_wait(bars + 8 * B_F2, 0);
        const uint32_t e1 = lds32(sb + OFF_SC + 4 * SC_EPOCH) + 1;
        if ((int)((lds32(sb + OFF_FL) - e1 * 8) | (lds32(sb + OFF_FL + 16) - e1 * NAUX)) < 0) { flag_wait(C_O + g, e1 * 8); flag_wait(C_AUX, e1 * NAUX); }
        const int j = fresh_cta() & 7, n0 = min(j, 6) * 8 * KB;
        const uint8_t* src = g_act + (size_t)g * G_STRIDE + G_O;
        mbar_expect(bars + 8 * B_WO, 56 * KB);
        if (j) bulk_g2s(sb + OFF_RING, src, n0, bars + 8 * B_WO);
        if (j < 6) bulk_g2s(sb + OFF_RING + n0, src + n0 + 8 * KB, 48 * KB - n0, bars + 8 * B_WO);
        bulk_g2s(sb + 44 * KB, src + (j == 7 ? 48 : 56) * KB, 8 * KB, bars + 8 * B_WO);
      }
    }
    if (it == 1) mbar_arrive(bars + 8 * B_F2);
    else if (it == 2) {
      asm volatile("atom.relaxed.cta.shared::cta.add.u32 %0, [%1], 1;" : "=r"(old) : "r"(sb + OFF_SC + 4 * SC_FREE) : "memory");
      if (old == 15) {
        const int j = fresh_cta() & 7;
        mbar_expect(bars + 8 * B_WO, 64 * KB);
        tma2d(sb + OFF_WO, &P.two, 64 * j, 0, bars + 8 * B_WO);
        tma2d(sb + OFF_WO + 32 * KB, &P.two, 64 * j, 256, bars + 8 * B_WO);
        mbar_expect(bars + 8 * B_W1F, 44 * KB);
        bulk_g2s(sb, g_w1t + j * 176 * KB, 44 * KB, bars + 8 * B_W1F);
      }
    }
  }
  __syncwarp();
}

__device__ __forceinline__ void publish_o(const float (&o)[12], uint32_t sb, int t, int wg, bool storer) {
  float i0, i1;
  asm("rcp.approx.ftz.f32 %0, %1;" : "=f"(i0) : "f"(o[8]));
  asm("rcp.approx.ftz.f32 %0, %1;" : "=f"(i1) : "f"(o[10]));
  const uint32_t stg = sb + OFF_Q + (t * 4 + wg) * 2048;
  const int tid = fresh_tid(), cta = fresh_cta();
  const uint32_t p0 = pack_bf16(o[0] * i0, o[1] * i0), p1 = pack_bf16(o[2] * i1, o[3] * i1), p2 = pack_bf16(o[4] * i0, o[5] * i0), p3 = pack_bf16(o[6] * i1, o[7] * i1);
  uint8_t* dst = g_act + (size_t)(cta >> 3) * G_STRIDE + G_O + t * 65536 + (8 * (cta & 7) + 2 * wg) * 1024;
  dst += (tid & 96) * 8 + (tid & 31) * 4;
  stsm4(stg + stsm_off(tid), p0, p1, p2, p3);
  if (t == 0) fence_async_smem();
  stg32(dst, p0); stg32(dst + 128, p1); stg32(dst + 1024, p2); stg32(dst + 1152, p3);
  if (t && elect_one()) hint_add(C_OB + (cta >> 3), cta & 7);
  if (storer && t == 0) asm volatile("cp.async.bulk.commit_group;\ncp.async.bulk.wait_group 0;" ::: "memory");
  __syncwarp();
  if (elect_one()) { mbar_arrive(sb + OFF_BAR + 8 * (t ? B_ADONE : B_OA)); if (t && storer) TSTAMP(32 + wg); }
  __syncwarp();
}
__device__ __forceinline__ void start_fills(uint32_t sb, int wg, bool storer) {
  if (storer) {
    if (elect_one()) {
      const int cta = fresh_cta(), j = cta & 7, hf = wg & 1;
      uint8_t* act = g_act + (size_t)(cta >> 3) * G_STRIDE;
      bulk_s2g(act + G_O + 65536 + (8 * j + 2 * wg) * 1024, sb + OFF_FILL, 2048);
      bulk_s2g(act + (wg < 2 ? G_H + (hf * 8 + j) * 8192 : G_HH + (hf * 172 + (f_start(j) >> 3)) * 1024), sb + OFF_FILL, wg < 2 ? 8 * KB : 22 * KB);
      if (wg < 2) bulk_s2g(act + G_ST + (hf * 8 + j) * 512, sb + OFF_FILL, 512);
    }
    __syncwarp();
  }
}
__device__ __forceinline__ void attention_fast(const Params& P, uint32_t sb, int wg, int duty, bool storer) {
  uint32_t c1 = P.c1, c2 = P.c2, c3 = P.c3;
  asm volatile("" : "+r"(c1), "+r"(c2), "+r"(c3));
#pragma unroll 1
  for (int t = 0; t < 2; t++) {
    float o[12], sA[32], sB[32];
    uint32_t pX[8], pY[8];
    const uint64_t dQ = mkdesc(sb + OFF_Q + (t * 4 + wg) * 2048, 1024, 128);
    uint64_t dK = mkdesc(sb, 4096, 128), dV = mkdesc(sb + 8192, 128, 4096);
#pragma unroll
    for (int i = 0; i < 12; i++) o[i] = 0.f;
#pragma unroll
    for (int i = 0; i < 16; i++) { sA[2 * i] = sA[2 * i + 1] = sB[2 * i] = sB[2 * i + 1] = initv(i); }
    pin(o); pin(sA); pin(sB);
    if (t == 0) mbar_wait(sb + OFF_BAR + 8 * B_KV0, 0);
    wg_fence();
    wgmma_qk_f16(sA, dQ, dK, 1);
    wgmma_qk_f16(sB, dQ, dK + 64, 1);
    wg_commit();
    if (t == 0) start_fills(sb, wg, storer);
    wg_wait<0>();
#pragma unroll 1
    for (int it = 0; it < 4; it++) {
      pin(sA); pin(sB);
#pragma unroll
      for (int j = 0; j < 8; j++) {
        float(&s)[32] = (j & 1) ? sB : sA;
        const int voff = (j >> 2) * (CHB / 16) + (j & 3) * 64, koff = ((j + 2) >> 2) * (CHB / 16) + ((j + 2) & 3) * 64;
        if (j > 0) wg_wait<1>();
        pin(s); pin(pX);
        exp_half<0>(s, pX, c1, c2, c3);
        pin(pX);
        wg_fence();
        wgmma_pv(o, pX[0], pX[1], pX[2], pX[3], dV + voff);
        wgmma_pv(o, pX[4], pX[5], pX[6], pX[7], dV + voff + 16);
        wg_commit();
        if (j > 0) wg_wait<1>();
        pin(pY);
        exp_half<1>(s, pY, c1, c2, c3);
        pin(pY);
        wg_fence();
        wgmma_pv(o, pY[0], pY[1], pY[2], pY[3], dV + voff + 32);
        wgmma_pv(o, pY[4], pY[5], pY[6], pY[7], dV + voff + 48);
        wgmma_qk_f16(s, dQ, dK + koff, 1);
        wg_commit();
      }
      dK += 2 * (CHB / 16); dV += 2 * (CHB / 16);
      wg_wait<0>();
      if (t == 0) { if (it == 0) mbar_wait(sb + OFF_BAR + 8 * B_KV1, 0); }
      else if (it < 3 && (it || duty)) region_freed(P, sb, it, duty & (it ? 2 : 1));
    }
    pin(o); pin(pX); pin(pY);
    publish_o(o, sb, t, wg, storer);
  }
}

__device__ __forceinline__ void attention_safe(const Params& P, uint32_t sb, int wg, int duty, bool storer) {
  start_fills(sb, wg, storer);
#pragma unroll 1
  for (int t = 0; t < 2; t++) {
    float o[12], s[32], m0 = -INFINITY, m1 = -INFINITY;
    uint32_t p[16];
    const uint64_t dQ = mkdesc(sb + OFF_Q + (t * 4 + wg) * 2048, 1024, 128);
#pragma unroll
    for (int i = 0; i < 12; i++) o[i] = 0.f;
#pragma unroll
    for (int i = 0; i < 32; i++) s[i] = 0.f;
#pragma unroll 1
    for (int j = 0; j < 32; j++) {
      const uint32_t base = sb + (j >> 2) * CHB + (j & 3) * 1024;
      pin(s);
      wg_fence();
      wgmma_qk_bf16(s, dQ, mkdesc(base, 4096, 128), 0);
      wg_commit();
      wg_wait<0>();
      pin(s);
      float n0 = m0, n1 = m1;
#pragma unroll
      for (int i = 0; i < 16; i++) {
        const uint32_t r = pack_bf16(s[2 * i], s[2 * i + 1]);
        s[2 * i] = bf_lo(r); s[2 * i + 1] = bf_hi(r);
        if (i & 1) n1 = fmaxf(n1, fmaxf(s[2 * i], s[2 * i + 1])); else n0 = fmaxf(n0, fmaxf(s[2 * i], s[2 * i + 1]));
      }
      n0 = fmaxf(n0, __shfl_xor_sync(~0u, n0, 1)); n0 = fmaxf(n0, __shfl_xor_sync(~0u, n0, 2));
      n1 = fmaxf(n1, __shfl_xor_sync(~0u, n1, 1)); n1 = fmaxf(n1, __shfl_xor_sync(~0u, n1, 2));
      const float r0 = ex2((m0 - n0) * QK_SCALE_LOG2), r1 = ex2((m1 - n1) * QK_SCALE_LOG2);
      m0 = n0; m1 = n1;
#pragma unroll
      for (int i = 0; i < 12; i++) o[i] *= (i & 2) ? r1 : r0;
#pragma unroll
      for (int i = 0; i < 16; i++) {
        const float mm = (i & 1) ? m1 : m0;
        p[i] = pack_bf16(ex2((s[2 * i] - mm) * QK_SCALE_LOG2), ex2((s[2 * i + 1] - mm) * QK_SCALE_LOG2));
      }
      pin(o); pin(p);
      wg_fence();
      const uint64_t dV = mkdesc(base + 8192, 128, 4096);
#pragma unroll
      for (int k = 0; k < 4; k++) wgmma_pv(o, p[4 * k], p[4 * k + 1], p[4 * k + 2], p[4 * k + 3], dV + 16 * k);
      wg_commit();
      wg_wait<0>();
      pin(o); pin(p);
      if (t == 1 && (j & 7) == 7 && j < 24) region_freed(P, sb, j >> 3, duty & (j > 7 ? 2 : 1));
    }
    publish_o(o, sb, t, wg, storer);
  }
}

__device__ __forceinline__ void aux_cta(const Params& P, uint8_t* smem) {
  const int a = blockIdx.x - NMAIN, tid = threadIdx.x, warp = tid >> 5, lane = tid & 31;
  const uint32_t sb = s2u(smem), bars = sb + OFF_BAR;
  { const long long t0 = clock64(); while (clock64() - t0 < 3000) {} }
  constexpr int PITCH = 43 * 16;
  if (tid == 0) {
#pragma unroll
    for (int i = 0; i < 4; i++) mbar_init(bars + 8 * i, 128);
  }
  fence_async_smem();
  __syncthreads();
  const int rr = warp * 8 + (lane & 7);
  const __nv_bfloat16* wsrc = P.w1 + (size_t)rr * F_ + a * 344;
  if (lane < 16) {
    mbar_expect(bars + (lane & 8), 688);
    bulk_g2s(sb + ((lane >> 3) * 128 + rr) * PITCH, wsrc + (lane >> 3) * 128 * F_, 688, bars + (lane & 8));
  }
  if (tid == 0) TSTAMP(1);
  float acc[3][8];
#pragma unroll
  for (int q = 0; q < 3; q++)
#pragma unroll
    for (int i = 0; i < 8; i++) acc[q][i] = 0.f;
#pragma unroll 1
  for (int h = 0; h < 4; h++) {
    mbar_wait(bars + 8 * h, 0);
#pragma unroll
    for (int q = 0; q < 3; q++) {
      const int blk = warp + 16 * q;
      if (blk < 43) {
        const int hb = (a & 1) * 43 + blk, n4 = min(hb / 22, 3);
        const int j0 = 2 * n4 + (a >> 1), j1 = 6 + (a >> 1);
        const int d0 = (j0 * 176 + hb - (n4 == 3 ? 64 : 22 * n4)) * KB;
        const int d1 = (hb == 64 || hb == 65) ? (j1 * 176 + hb - 64) * KB : -1;
#pragma unroll
        for (int u = 0; u < 4; u++) {
          const int r = u * 32 + lane;
          const uint4 w = *(const uint4*)(smem + ((h & 1) * 128 + r) * PITCH + blk * 16);
          uint8_t* dst = g_w1t + (r & 63) * 16;
          *(uint4*)(dst + d0 + ((h * 2 + (u >> 1) - j0) & 7) * 22 * KB) = w;
          if (d1 >= 0) *(uint4*)(dst + d1 + ((h * 2 + (u >> 1) - j1) & 7) * 22 * KB) = w;
          acc[q][0] += bf_lo(w.x); acc[q][1] += bf_hi(w.x); acc[q][2] += bf_lo(w.y); acc[q][3] += bf_hi(w.y);
          acc[q][4] += bf_lo(w.z); acc[q][5] += bf_hi(w.z); acc[q][6] += bf_lo(w.w); acc[q][7] += bf_hi(w.w);
        }
      }
    }
    __syncthreads();
    if (h < 2 && lane < 8) {
      mbar_expect(bars + 8 * (h + 2), 688);
      bulk_g2s(sb + (h * 128 + rr) * PITCH, wsrc + (h + 2) * 128 * F_, 688, bars + 8 * (h + 2));
    }
    if (h == 2 && lane == 0) {
      l2_prefetch((const uint8_t*)P.wo + (size_t)(a * 16 + warp) * 8192, 8192);
      l2_prefetch((const uint8_t*)P.w2 + (size_t)(a * 16 + warp) * 22016, 22016);
    }
  }
  if (tid == 0) TSTAMP(2);
#pragma unroll
  for (int q = 0; q < 3; q++) {
#pragma unroll
    for (int i = 0; i < 8; i++)
#pragma unroll
      for (int o = 1; o < 32; o <<= 1) acc[q][i] += __shfl_xor_sync(~0u, acc[q][i], o);
    if (warp + 16 * q < 43 && lane == 0) {
      uint32_t hi[4], lo[4];
#pragma unroll
      for (int i = 0; i < 4; i++) {
        hi[i] = pack_bf16(acc[q][2 * i], acc[q][2 * i + 1]);
        lo[i] = pack_bf16(acc[q][2 * i] - bf_lo(hi[i]), acc[q][2 * i + 1] - bf_hi(hi[i]));
      }
      uint4* dst = g_cs1 + (a * 43 + warp + 16 * q) * 3;
      dst[0] = dst[1] = make_uint4(hi[0], hi[1], hi[2], hi[3]);
      dst[2] = make_uint4(lo[0], lo[1], lo[2], lo[3]);
    }
  }
  __syncthreads();
  if (tid == 0) { flag_add(C_AUX); flag_add(C_DONE); TSTAMP(0); }
}

__device__ __forceinline__ void kv_path(uint8_t* smem, uint32_t sb, const uint4 (&xr)[4]) {
  const int t = threadIdx.x - 256, w = t >> 5, lane = t & 31, g8 = lane >> 2, c = lane & 3;
  uint32_t xa[16] = {xr[0].x, xr[0].y, xr[0].z, xr[0].w, xr[2].x, xr[2].y, xr[2].z, xr[2].w,
                     xr[1].x, xr[1].y, xr[1].z, xr[1].w, xr[3].x, xr[3].y, xr[3].z, xr[3].w};
  if (c & 1) {
#pragma unroll
    for (int i = 0; i < 16; i += 2) { const uint32_t tmp = xa[i]; xa[i] = xa[i + 1]; xa[i + 1] = tmp; }
  }
  float s0 = 0, q0 = 0, s1 = 0, q1 = 0;
#pragma unroll
  for (int i = 0; i < 8; i++) {
    float a = bf_lo(xa[i]), b = bf_hi(xa[i]); s0 += a + b; q0 = fmaf(a, a, fmaf(b, b, q0));
    a = bf_lo(xa[8 + i]); b = bf_hi(xa[8 + i]); s1 += a + b; q1 = fmaf(a, a, fmaf(b, b, q1));
  }
  s0 += __shfl_xor_sync(~0u, s0, 1); q0 += __shfl_xor_sync(~0u, q0, 1); s1 += __shfl_xor_sync(~0u, s1, 1); q1 += __shfl_xor_sync(~0u, q1, 1);
  s0 += __shfl_xor_sync(~0u, s0, 2); q0 += __shfl_xor_sync(~0u, q0, 2); s1 += __shfl_xor_sync(~0u, s1, 2); q1 += __shfl_xor_sync(~0u, q1, 2);
  uint8_t* stg = g_kv + blockIdx.x * 16;
  float4* pst = (float4*)(smem + OFF_KVS);
  if (c == 0) pst[w * 8 + g8] = make_float4(s0, q0, s1, q1);
  bar_sync(12, 288);
  {
    const float4 u = pst[c * 16 + g8], v = pst[c * 16 + 8 + g8];
    s0 = u.x + v.x; q0 = u.y + v.y; s1 = u.z + v.z; q1 = u.w + v.w;
  }
  s0 += __shfl_xor_sync(~0u, s0, 1); q0 += __shfl_xor_sync(~0u, q0, 1); s1 += __shfl_xor_sync(~0u, s1, 1); q1 += __shfl_xor_sync(~0u, q1, 1);
  s0 += __shfl_xor_sync(~0u, s0, 2); q0 += __shfl_xor_sync(~0u, q0, 2); s1 += __shfl_xor_sync(~0u, s1, 2); q1 += __shfl_xor_sync(~0u, q1, 2);
  const float mean0 = s0 * (1.0f / D_), rstd0 = rsqrtf(fmaxf(q0 * (1.0f / D_) - mean0 * mean0, 0.f) + LN_EPS);
  const float mean1 = s1 * (1.0f / D_), rstd1 = rsqrtf(fmaxf(q1 * (1.0f / D_) - mean1 * mean1, 0.f) + LN_EPS);
  if (w == 0 && c == 0) {
    *(float2*)(stg + (R_ST + (g8 >> 1)) * 2048 + (g8 & 1) * 8) = make_float2(mean0, rstd0);
    *(float2*)(stg + (R_ST + 4 + (g8 >> 1)) * 2048 + (g8 & 1) * 8) = make_float2(mean1, rstd1);
  }
  float d[4][4], e[4][4];
#pragma unroll
  for (int i = 0; i < 4; i++)
#pragma unroll
    for (int k = 0; k < 4; k++) { d[i][k] = 0.f; e[i][k] = 0.f; }
  const uint32_t one = 0x3F803F80u;
  const uint32_t la = sb + OFF_WKV + (64 * w + 8 * ((lane & 7) >> 1) + 2 * (((lane >> 3) ^ (lane >> 1)) & 1) + (lane & 1)) * 32 + (((lane >> 4) ^ (lane >> 2)) & 1) * 16;
  mbar_wait(sb + OFF_BAR + 8 * B_WKV, 0);
  if (t == 0) TSTAMP(23);
#pragma unroll
  for (int ks = 0; ks < 4; ks++) {
    const uint32_t a0 = xa[2 * ks], a1 = xa[8 + 2 * ks], a2 = xa[2 * ks + 1], a3 = xa[9 + 2 * ks];
#pragma unroll
    for (int m = 0; m < 2; m++) {
      uint32_t bw[4];
      ldsm4t(bw, la + (32 * (ks >> 1) + 4 * (ks & 1)) * 32 + m * 16 * KB);
      const uint32_t b0 = c & 2 ? bw[2] : bw[0], b1 = c & 2 ? bw[3] : bw[1], b2 = c & 2 ? bw[0] : bw[2], b3 = c & 2 ? bw[1] : bw[3];
      mma16816(d[2 * m], a0, a1, a2, a3, b0, b1); mma16816(d[2 * m + 1], a0, a1, a2, a3, b2, b3);
      mma16816(e[2 * m], one, one, one, one, b0, b1); mma16816(e[2 * m + 1], one, one, one, one, b2, b3);
    }
  }
  __syncwarp();
  float* pw = (float*)(smem + OFF_WKV + w * 2048) + g8 * 18 + 2 * c;
#pragma unroll
  for (int i = 0; i < 4; i++) {
    *(float2*)(pw + (i >> 1) * 4096 + (i & 1) * 8) = make_float2(rstd0 * (d[i][0] - mean0 * e[i][0]), rstd0 * (d[i][1] - mean0 * e[i][1]));
    *(float2*)(pw + (i >> 1) * 4096 + (i & 1) * 8 + 144) = make_float2(rstd1 * (d[i][2] - mean1 * e[i][0]), rstd1 * (d[i][3] - mean1 * e[i][1]));
  }
  bar_sync(1, 256);
  const int row = lane & 15, cp = (2 * w + (lane >> 4)) & 7;
  float ax = 0, ay = 0;
  const float* pr = (const float*)(smem + OFF_WKV) + (w >> 2) * 4096 + 2 * cp + row * 18;
#pragma unroll
  for (int i = 0; i < 8; i++) { const float2 a = *(const float2*)(pr + i * 512); ax += a.x; ay += a.y; }
  uint32_t val = pack_bf16(ax, ay);
  float v0 = bf_lo(val), v1 = bf_hi(val);
  float nn = v0 * v0 + v1 * v1;
  nn += __shfl_xor_sync(~0u, nn, 16);
  const int sub = (cp >> 2) * 2 + (row & 1);
  if (w < 4) {
    *(uint32_t*)(stg + (R_KP + (row >> 1) * 4 + sub) * 2048 + (cp & 3) * 4) = val;
    const float m = fmaxf(fabsf(v0), fabsf(v1));
    const float m3 = fmaxf(m, fmaxf(__shfl_up_sync(~0u, m, 1, 16), __shfl_down_sync(~0u, m, 1, 16)));
    const float magic = __uint_as_float((__float_as_uint(m3) & 0x7F800000u) + (14u << 23) + 0x00400000u);
    v0 = (v0 + magic) - magic; v1 = (v1 + magic) - magic;
    const float p0 = __shfl_up_sync(~0u, v0, 1, 16), p1 = __shfl_up_sync(~0u, v1, 1, 16);
    val = row ? pack_f16(v0 - p0, v1 - p1) : pack_f16(v0, v1);
  } else if (cp < 4) {
    *(uint32_t*)(stg + ((row >> 1) * 10 + 8 + (row & 1)) * 2048 + cp * 4) = 0x3F803F80u;
  }
  *(uint32_t*)(stg + ((row >> 1) * 10 + (w >> 2) * 4 + sub) * 2048 + (cp & 3) * 4) = val;
  const uint32_t nmax = __reduce_max_sync(~0u, __float_as_uint(nn));
  if (lane == 0) *(uint32_t*)(stg + (R_MX + (w >> 2)) * 2048 + (w & 3) * 4) = nmax;
  bar_sync(7, 320);
}

__device__ __forceinline__ void post_chain(const Params& P, uint8_t* smem, uint32_t sb, int hf) {
  const int tid = fresh_tid() & 127, warp = tid >> 5, lane = tid & 31, g8 = lane >> 2, c = lane & 3;
  const int cta = fresh_cta(), g = cta >> 3, j = cta & 7, gh = g * 2 + hf;
  const uint32_t bars = sb + OFF_BAR;
  const int row0 = g * 128 + hf * 64 + warp * 16 + g8;
  uint8_t* act = g_act + (size_t)g * G_STRIDE;
  const int frag = warp * 256 + lane * 4;
  const bool lead = elect_one();
  const uint32_t rf = bars + 8 * (B_RF + 6 * hf);
  const uint64_t dA = mkdesc(sb, 1024, 128);
  if (tid == 0) mbar_expect(bars + 8 * (B_RED + hf), 16 * KB);
  {
    uint32_t xr[16];
    const uint32_t* xp = (const uint32_t*)(P.x + (size_t)row0 * D_ + 64 * j + 2 * c);
#pragma unroll
    for (int b = 0; b < 8; b++) { xr[2 * b] = __ldg(xp + 4 * b); xr[2 * b + 1] = __ldg(xp + 8 * 256 + 4 * b); }
    float acc[32];
    undef(acc);
    mbar_wait2(bars + 8 * (hf ? B_ADONE : B_WO), 0, bars + 8 * B_WO);
    if (hf) fence_async_smem();
    if (tid == 0 && hf == 0) TSTAMP(29);
    const uint64_t dw = mkdesc(sb + OFF_WO, 8192, 1024, 1);
    wg_fence();
#pragma unroll
    for (int s = 0; s < 4; s++) wgmma_n64_bt(acc, dA + ((OFF_Q + hf * 8 * KB) >> 4) + 128 * s, dw + 512 * j + 128 * s, s);
    wg_commit();
#pragma unroll
    for (int k = 0; k < 7; k++) {
      const int u = hf ? k : (k + 6) % 7;
      const uint64_t da = dA + (u == 6 ? 44 * 64 : (hf ? 120 * 64 : OFF_RING >> 4) + 512 * u), db = dw + 512 * (u < j ? u : u + 1);
      if (hf) mbar_wait(k < 6 ? rf + 8 * k : bars + 8 * B_OX, 0);
      else { wg_wait<0>(); if (k == 1 && lead) mbar_arrive(bars + 8 * B_OWN); }
      wg_fence();
#pragma unroll
      for (int s = 0; s < 4; s++) wgmma_n64_bt(acc, da + 128 * s, db + 128 * s, 1);
      wg_commit();
    }
    wg_wait<0>();
    pin(acc);
    if (lane < 6 && (lane == 0 || !hf)) mbar_arrive(bars + 8 * (lane ? B_RE + lane : B_PDONE));
    redo_gemm<8>(acc, act + G_O + hf * 65536 + (warp * 16 + g8) * 16, D_, P.wo + 64 * j + 2 * c, D_, 0);
    if (tid == 0) TSTAMP(30 + hf);
#pragma unroll
    for (int b = 0; b < 8; b++) {
      xr[2 * b] = pack_bf16(acc[4 * b] + bf_lo(xr[2 * b]), acc[4 * b + 1] + bf_hi(xr[2 * b]));
      xr[2 * b + 1] = pack_bf16(acc[4 * b + 2] + bf_lo(xr[2 * b + 1]), acc[4 * b + 3] + bf_hi(xr[2 * b + 1]));
      stg32(act + G_H + (hf * 8 + j) * 8192 + frag + b * 1024, xr[2 * b]);
      stg32(act + G_H + (hf * 8 + j) * 8192 + frag + b * 1024 + 128, xr[2 * b + 1]);
    }
    if (lead) { hint_add(C_H + gh, j); mbar_arrive(bars + 8 * (B_SA + hf)); if (warp == 3) TSTAMP(40 + hf); }
    __syncwarp();
    pin(xr);
#pragma unroll
    for (int s = 0; s < 4; s++) stsm4(sb + (hf ? 120 * KB : OFF_RING) + stsm_off(tid) + s * 2048, xr[4 * s], xr[4 * s + 1], xr[4 * s + 2], xr[4 * s + 3]);
    float s0 = 0, q0 = 0, s1 = 0, q1 = 0;
#pragma unroll
    for (int b = 0; b < 8; b++) {
      float u = bf_lo(xr[2 * b]), v = bf_hi(xr[2 * b]); s0 += u + v; q0 = fmaf(u, u, fmaf(v, v, q0));
      u = bf_lo(xr[2 * b + 1]); v = bf_hi(xr[2 * b + 1]); s1 += u + v; q1 = fmaf(u, u, fmaf(v, v, q1));
    }
    s0 += __shfl_xor_sync(~0u, s0, 1); q0 += __shfl_xor_sync(~0u, q0, 1); s1 += __shfl_xor_sync(~0u, s1, 1); q1 += __shfl_xor_sync(~0u, q1, 1);
    s0 += __shfl_xor_sync(~0u, s0, 2); q0 += __shfl_xor_sync(~0u, q0, 2); s1 += __shfl_xor_sync(~0u, s1, 2); q1 += __shfl_xor_sync(~0u, q1, 2);
    stg32(act + G_ST + (hf * 8 + j) * 512 + tid * 4, __float_as_uint(c == 0 ? s0 : c == 1 ? q0 : c == 2 ? s1 : q1));
    fence_async_smem();
  }
  if (tid == 0) TSTAMP(8 + hf * 8);
  {
    float acc[88];
    undef(acc);
#define RSLOT(r0, r1) ((r0) % 6 + hf * ((r1) % 6 - (r0) % 6))
#define RPAR(r0, r1) ((int)(RING_PAR >> (r0) & 1) + hf * ((int)(RING_PAR >> (r1) & 1) - (int)(RING_PAR >> (r0) & 1)))
    const uint64_t dR = dA + (OFF_RING >> 4), dW = mkdesc(sb, 128, 1024);
    mbar_wait(bars + 8 * B_W1F, 0);
    wg_fence();
#pragma unroll
    for (int s = 0; s < 4; s++) wgmma_n176_bt(acc, dA + (hf ? 120 * 64 : OFF_RING >> 4) + 128 * s, dW + 16 * s, s);
    wg_commit();
    wg_wait<0>();
    if (lane < 2 - hf) mbar_arrive(bars + 8 * (lane ? B_RE : B_W1E));
    mbar_wait(rf + 8 * RSLOT(12, 19), RPAR(12, 19));
    if (tid == 0) TSTAMP(13 + hf * 8);
    wg_fence();
#pragma unroll
    for (int k = 1; k < 8; k++) {
      const uint64_t da = dR + 512 * RSLOT(11 + k, 18 + k), db = dW + ((W1_SLOT >> (4 * k)) & 7) * 1408;
      wgmma_n176_bt(acc, da, db, 1);
      wgmma_n176_bt(acc, da + 128, db + 16, 1);
      wg_commit();
      if (k > 1) {
        wg_wait<1>();
        if (lane < 2) mbar_arrive(bars + 8 * (lane ? B_W1E + k - 1 : B_RE + RSLOT(10 + k, 17 + k)));
      }
      wgmma_n176_bt(acc, da + 256, db + 32, 1);
      wg_commit();
      if (k < 7) mbar_wait2(rf + 8 * RSLOT(12 + k, 19 + k), RPAR(12 + k, 19 + k), bars + 8 * (B_W1F + k + 1));
      else mbar_wait(bars + 8 * (B_ST2 + hf), 0);
      if (k == 7 && !hf && lead) mbar_arrive(bars + 8 * B_OWN);
      if (k == 1 && hf) mbar_wait(bars + 8 * B_OWN, 1);
      wg_fence();
      wgmma_n176_bt(acc, da + 384, db + 48, 1);
      wg_commit();
    }
    const float4 ln = *(const float4*)(smem + OFF_ST2 + hf * 512 + (tid >> 2) * 16);
    const float hr0 = ln.x, hr1 = ln.z;
    uint32_t am[2] = {__float_as_uint(ln.y), __float_as_uint(ln.w)};
    const uint32_t keep = c == 0 ? ~0u : c == 1 ? 0xFFFFu : 0u;
    am[0] &= keep; am[1] &= keep;
    pin(am);
    wg_fence();
    wgmma_r176(acc, am[0], am[1], 0, 0, mkdesc(sb + OFF_CS, 0, 48));
    wg_commit();
    wg_wait<0>();
    pin(acc);
    if (lane < 2) mbar_arrive(bars + 8 * (lane ? B_W1E + 7 : B_RE + RSLOT(18, 25)));
    redo_gemm<22>(acc, act + G_H + hf * 65536 + (warp * 16 + g8) * 16, D_, P.w1 + f_start(j) + 2 * c, F_, 0,
                  bf_lo(__float_as_uint(ln.y)) + bf_hi(__float_as_uint(ln.y)), bf_lo(__float_as_uint(ln.w)) + bf_hi(__float_as_uint(ln.w)));
    if (tid == 0) TSTAMP(9 + hf * 8);
    const int o = (j >> 1) % 3;
    const uint32_t stg = sb + (hf ? 112 * KB : 0) - o * 2048;
    uint32_t hp[12];
    uint8_t* hdst = act + G_HH + (hf * 172 + (f_start(j) >> 3)) * 1024 + frag;
#pragma unroll
    for (int b = 0; b < 22; b++) {
      float v[4] = {acc[4 * b] * hr0, acc[4 * b + 1] * hr0, acc[4 * b + 2] * hr1, acc[4 * b + 3] * hr1};
#pragma unroll
      for (int i = 0; i < 4; i++) {
        float th; asm("tanh.approx.f32 %0, %1;" : "=f"(th) : "f"(v[i]));
        v[i] = fmaf(v[i], th, v[i]);
      }
      const int q = b < 6 ? 2 * b : 2 * (b & 1);
      hp[q] = pack_bf16(v[0], v[1]);
      hp[q + 1] = pack_bf16(v[2], v[3]);
      if (b < 20 || o != 2) { stg32(hdst + b * 1024, hp[q]); stg32(hdst + b * 1024 + 128, hp[q + 1]); }
      if ((b == 11 || b == 21) && lead) {
        hint_add(C_HH + gh, j + (b == 11 ? 8 : 0));
        mbar_arrive(bars + 8 * ((b == 11 ? B_S1 : B_SH) + hf));
        if (warp == 3) TSTAMP((b == 11 ? 56 : 42) + hf);
      }
      if (b == 5) {
        pin(hp);
        mbar_wait(bars + 8 * (B_W1E + 7 * hf), 0);
#pragma unroll
        for (int s = 0; s < 3; s++) if (s >= o) stsm4(stg + stsm_off(tid) + s * 2048, hp[4 * s], hp[4 * s + 1], hp[4 * s + 2], hp[4 * s + 3]);
      } else if (b > 5 && b < 20 && (b & 1)) {
        if ((b >> 1) < 8 + o) stsm4(stg + stsm_off(tid) + (b >> 1) * 2048, hp[0], hp[1], hp[2], hp[3]);
      }
    }
    fence_async_smem();
  }
  if (tid == 0) TSTAMP(10 + hf * 8);
  {
    float acc[64];
    undef(acc);
    uint32_t hr[16];
    const uint8_t* himg = act + G_H + (hf * 8 + j) * 8192 + frag;
#pragma unroll
    for (int b = 0; b < 8; b++) { hr[2 * b] = __ldcg((const uint32_t*)(himg + b * 1024)); hr[2 * b + 1] = __ldcg((const uint32_t*)(himg + b * 1024 + 128)); }
    const int kh = j & 1;
    uint32_t peer;
    asm volatile("mapa.shared::cluster.u32 %0, %1, %2;" : "=r"(peer) : "r"(sb), "r"(kh ^ 1));
    const uint64_t dR = dA + (OFF_RING >> 4), dW = mkdesc(sb, 0, 1024, 1);
    {
      const uint64_t da = dA + (hf ? 112 * 64 : 0);
      mbar_wait2(bars + 8 * B_W2F, 0, bars + 8 * (B_W2F + 1));
      wg_fence();
#pragma unroll
      for (int s = 0; s < 8; s++) wgmma_n128_bt(acc, da + 128 * s, dW + ((s < 4 ? 3 : 17) * 512 + (1 << 25) + 128 * (s & 3)), s);
      wg_commit();
      wg_wait<0>();
      if (lead) {
        mbar_arrive(bars + 8 * (B_SW + hf));
        asm volatile("mbarrier.arrive.relaxed.cluster.shared::cluster.b64 _, [%0];" ::"r"(peer + OFF_BAR + 8 * B_LAND) : "memory");
      }
    }
    mbar_wait2(rf + 8 * RSLOT(26, 35), RPAR(26, 35), bars + 8 * (B_W2F + 2));
    if (tid == 0) TSTAMP(14 + hf * 8);
    wg_fence();
#pragma unroll
    for (int i = 2; i < 11; i++) {
      const uint32_t a0 = (uint32_t)(W2_A0 >> (5 * i)) & 31, a1 = (uint32_t)(W2_A1 >> (5 * i)) & 31;
      const uint64_t da = dR + 512 * RSLOT(24 + i, 33 + i), db = dW + (a0 * 512 + ((a1 - a0) << 25));
      wgmma_n128_bt(acc, da, db, 1);
      wgmma_n128_bt(acc, da + 128, db + 128, 1);
      wg_commit();
      if (i > 2) {
        wg_wait<1>();
        if (lead) mbar_arrive(bars + 8 * (B_RE + RSLOT(23 + i, 32 + i)));
      }
      wgmma_n128_bt(acc, da + 256, db + 256, 1);
      wg_commit();
      if (i < 10) {
        mbar_wait2(rf + 8 * RSLOT(25 + i, 34 + i), RPAR(25 + i, 34 + i), bars + 8 * (B_W2F + i + 1));
        wg_fence();
        wgmma_n128_bt(acc, da + 384, db + 384, 1);
        wg_commit();
      }
    }
    mbar_wait(bars + 8 * B_LAND, 0);
    wg_wait<0>();
    pin(acc);
    redo_gemm<16>(acc, act + G_HH + (hf * 172 + kh * 86) * 1024 + (warp * 16 + g8) * 16, 688, P.w2 + (size_t)kh * 688 * D_ + 64 * j + 2 * c, D_, -128 * kh);
    if (tid == 0) TSTAMP(11 + hf * 8);
    const uint32_t land = (hf ? 136 : 24) * KB + tid * 16;
#pragma unroll
    for (int i = 0; i < 8; i++)
      asm volatile("st.async.shared::cluster.mbarrier::complete_tx::bytes.v4.f32 [%0], {%1,%2,%3,%4}, [%5];"
                   ::"r"(peer + land + i * 2048), "f"(acc[32 + 4 * i]), "f"(acc[33 + 4 * i]), "f"(acc[34 + 4 * i]), "f"(acc[35 + 4 * i]),
                     "r"(peer + OFF_BAR + 8 * (B_RED + hf)) : "memory");
    if (lead) mbar_arrive(bars + 8 * (B_RE + RSLOT(34, 43)));
    if (tid == 0) TSTAMP(58 + hf);
#pragma unroll
    for (int i = 0; i < 8; i++) {
      acc[4 * i] += bf_lo(hr[2 * i]); acc[4 * i + 1] += bf_hi(hr[2 * i]); acc[4 * i + 2] += bf_lo(hr[2 * i + 1]); acc[4 * i + 3] += bf_hi(hr[2 * i + 1]);
    }
    pin(acc);
    mbar_wait(bars + 8 * (B_RED + hf), 0);
    if (tid == 0) TSTAMP(60 + hf);
    float4 r[8];
#pragma unroll
    for (int i = 0; i < 8; i++) r[i] = *(const float4*)(smem + land + i * 2048);
    __syncwarp();
    const uint32_t ob = sb + land - lane * 16;
#pragma unroll
    for (int i = 0; i < 8; i += 2)
      stsm4(ob + (lane & 12) * 512 + (lane & 3) * 128 + (((i + (lane >> 4)) ^ (lane & 7)) << 4),
            pack_bf16(acc[4 * i] + r[i].x, acc[4 * i + 1] + r[i].y), pack_bf16(acc[4 * i + 2] + r[i].z, acc[4 * i + 3] + r[i].w),
            pack_bf16(acc[4 * i + 4] + r[i + 1].x, acc[4 * i + 5] + r[i + 1].y), pack_bf16(acc[4 * i + 6] + r[i + 1].z, acc[4 * i + 7] + r[i + 1].w));
    __syncwarp();
    uint4* op = (uint4*)(P.out + (size_t)(row0 - g8 + (lane >> 3)) * D_ + 64 * j) + (lane & 7);
#pragma unroll
    for (int i = 0; i < 4; i++) {
      uint4 v;
      asm volatile("ld.shared.v4.u32 {%0,%1,%2,%3}, [%4];" : "=r"(v.x), "=r"(v.y), "=r"(v.z), "=r"(v.w)
                   : "r"(ob + i * 2048 + (lane >> 3) * 128 + (((lane & 7) ^ ((4 * i + (lane >> 3)) & 7)) << 4)) : "memory");
      op[i * 256] = v;
    }
    if (tid == 0) TSTAMP(12 + hf * 8);
  }
}

__device__ __forceinline__ void ring_producer(uint32_t sb, int slot) {
  const int cta = fresh_cta(), g = cta >> 3, j = cta & 7, lane = fresh_tid() & 31;
  const uint32_t bars = sb + OFF_BAR, e1 = lds32(sb + OFF_SC + 4 * SC_EPOCH) + 1;
  const uint8_t* act = g_act + (size_t)g * G_STRIDE;
#pragma unroll 1
  for (int r = 6 + slot; r < 44; r += 6) {
    int hf, off, line, word, own;
    uint32_t bytes = 8 * KB, target = 4 * e1;
    if (r < 12) { hf = 1; word = r - 6 + (r - 6 >= j); off = G_O + 65536 + word * 8 * KB; line = C_OB + g; own = B_ADONE; target = 16 * e1; }
    else if (r < 26) { hf = r >= 19; word = (r - 11 - 7 * hf + j) & 7; off = G_H + (hf * 8 + word) * 8 * KB; line = C_H + 2 * g + hf; own = B_SA + hf; }
    else {
      hf = r >= 35;
      const int p = r - 24 - 9 * hf, i = k2_chunk(j, p);
      word = 2 * min((4 * i + (p < 5 ? 3 : 3 * (lane & 1))) / 11, 3) + (j & 1);
      off = G_HH + (hf * 172 + (j & 1) * 86 + 8 * i) * KB; line = C_HH + 2 * g + hf; own = (p < 5 ? B_S1 : B_SH) + hf;
      if (p < 5) word += 8;
      if (i == 10) bytes = 6 * KB;
    }
    const uint32_t fb = bars + 8 * (B_RF + 6 * hf + slot);
    mbar_wait(bars + 8 * own, 0);
    hint_wait(line, target, word);
    if (r >= 11) mbar_wait(bars + 8 * (r == 11 ? B_OWN : B_RE + slot), r < 12 ? 0 : (r / 6) & 1);
    if (r >= 20 && r < 25) mbar_wait(bars + 8 * (B_W1F + 6), 0);
    if (elect_one()) {
      mbar_expect(fb, bytes);
      bulk_g2s(sb + (r < 12 ? 120 * KB : OFF_RING) + slot * 8 * KB, act + off, bytes, fb);
    }
  }
}

__device__ __forceinline__ void ln2_stats(uint8_t* smem, uint32_t sb) {
  const int g = fresh_cta() >> 3, lane = fresh_tid() & 31;
  const uint32_t bars = sb + OFF_BAR, epoch = lds32(sb + OFF_SC + 4 * SC_EPOCH);
  {
    const int u = (fresh_cta() & 7) == 7 ? 6 : 7;
    mbar_wait(bars + 8 * B_ADONE, 0);
    hint_wait(C_OB + g, (epoch + 1) * 16, u);
    mbar_wait(bars + 8 * B_OWN, 0);
    if (elect_one()) {
      mbar_expect(bars + 8 * B_OX, 8 * KB);
      bulk_g2s(sb + 44 * KB, g_act + (size_t)g * G_STRIDE + G_O + 65536 + u * 8 * KB, 8 * KB, bars + 8 * B_OX);
    }
  }
#pragma unroll 1
  for (int hf = 0; hf < 2; hf++) {
    mbar_wait(bars + 8 * (B_RF + 6 * hf + 5), hf);
    const float4* sp = (const float4*)(g_act + (size_t)g * G_STRIDE + G_ST + hf * 4096) + lane;
    float4 a;
#pragma unroll 1
    for (int n = 0; n < 100000; n++) {
      uint32_t m = 0;
      a = make_float4(0.f, 0.f, 0.f, 0.f);
#pragma unroll
      for (int i = 0; i < 8; i++) {
        float4 v;
        asm volatile("ld.relaxed.gpu.global.v4.f32 {%0,%1,%2,%3}, [%4];" : "=f"(v.x), "=f"(v.y), "=f"(v.z), "=f"(v.w) : "l"(sp + 32 * i) : "memory");
        a.x += v.x; a.y += v.y; a.z += v.z; a.w += v.w;
        m = max(m, __float_as_uint(v.y));
      }
      if (!__any_sync(~0u, m == 0xFFFFFFFFu)) break;
    }
    const float mean0 = a.x * (1.0f / D_), hr0 = 0.5f * rsqrtf(fmaxf(a.y * (1.0f / D_) - mean0 * mean0, 0.f) + LN_EPS);
    const float mean1 = a.z * (1.0f / D_), hr1 = 0.5f * rsqrtf(fmaxf(a.w * (1.0f / D_) - mean1 * mean1, 0.f) + LN_EPS);
    *(float4*)(smem + OFF_ST2 + hf * 512 + lane * 16) = make_float4(hr0, __uint_as_float(split_bf16(-mean0)), hr1, __uint_as_float(split_bf16(-mean1)));
    __syncwarp();
    if (lane == 0) mbar_arrive(bars + 8 * (B_ST2 + hf));
  }
}

__device__ __forceinline__ void weight_producer(const Params& P, uint32_t sb) {
  const int j = fresh_cta() & 7;
  const uint32_t bars = sb + OFF_BAR;
  if (elect_one()) {
    mbar_arrive(bars + 8 * (B_W1F + 1));
    fence_async_all();
#pragma unroll 1
    for (int k = 2; k < 8; k++) {
      mbar_wait2(bars + 8 * (k == 7 ? B_W1E : B_PDONE), 0, bars + 8 * (B_W1F + k - 2));
      if (k == 2) TSTAMP(15);
      mbar_expect(bars + 8 * (B_W1F + k), k == 2 ? 22 * KB + 1136 : 22 * KB);
      if (k == 2) bulk_g2s(sb + OFF_CS, g_cs1 + (f_start(j) >> 3) * 3, 1136, bars + 8 * (B_W1F + 2));
      load_w1(sb, j, k);
    }
    const int n0 = j * 64, k0 = (j & 1) * 688;
#pragma unroll 1
    for (int i = 0; i < 11; i++) {
      mbar_wait2(bars + 8 * (B_SW + (int)((W2_DEP >> (4 * i)) & 15)), 0, bars + 8 * (B_W2F + i - 2));
      const int kc = k0 + 64 * k2_chunk(j, i);
      mbar_expect(bars + 8 * (B_W2F + i), 16 * KB);
      tma2d(sb + ((uint32_t)(W2_A0 >> (5 * i)) & 31) * 8 * KB, &P.tw2, n0, kc, bars + 8 * (B_W2F + i));
      tma2d(sb + ((uint32_t)(W2_A1 >> (5 * i)) & 31) * 8 * KB, &P.tw2, n0 ^ 64, kc, bars + 8 * (B_W2F + i));
    }
  }
}

__global__ void __cluster_dims__(2, 1, 1) __launch_bounds__(512, 1) fused_block_kernel(const __grid_constant__ Params P) {
  extern __shared__ __align__(1024) uint8_t smem[];
  if (blockIdx.x >= NMAIN) { aux_cta(P, smem); return; }
  const uint32_t sb = s2u(smem), bars = sb + OFF_BAR;
  bool fast;
  {
    const int tid = threadIdx.x, lane = tid & 31;
    const int wid = __shfl_sync(~0u, tid >> 5, 0), wg = wid >> 2;
    const int bid = blockIdx.x, g = bid >> 3, j = bid & 7;
    uint32_t* sc = (uint32_t*)(smem + OFF_SC);
    float qacc[32];
    const uint32_t qdst = sb + OFF_Q + wg * 8192 + stsm_off(tid);
    if (wg < 2) {
      if (tid == 0) TSTAMP(0);
      if (wid == 1) {
        const bool el = elect_one();
        if (el) {
          mbar_init(bars + 8 * B_WKV, 1);
          mbar_expect(bars + 8 * B_WKV, 32 * KB);
          bulk_g2s(sb + OFF_WKV, P.wk, 16 * KB, bars + 8 * B_WKV);
          bulk_g2s(sb + OFF_WKV + 16 * KB, P.wv, 16 * KB, bars + 8 * B_WKV);
#pragma unroll
          for (int k = 0; k < 8; k++) mbar_init(bars + 8 * (B_XQ + k), 1);
        }
        __syncwarp();
        asm volatile("bar.arrive 12, 288;" ::: "memory");
        { const long long t0 = clock64(); while (clock64() - t0 < 1400) {} }
        if (elect_one()) {
#pragma unroll 1
          for (int k = 0; k < 8; k++) {
            mbar_expect(bars + 8 * (B_XQ + k), 24 * KB);
            tma2d(sb + OFF_X + 16 * KB * k, &P.tx, 64 * k, 128 * g, bars + 8 * (B_XQ + k));
            tma2d(sb + OFF_WQ + 8 * KB * k, &P.twq, 64 * j, 64 * k, bars + 8 * (B_XQ + k));
          }
        }
      } else {
        if (wid >= 3 && wid < 7 && elect_one()) asm volatile("prefetch.tensormap [%0];" ::"l"(&P.tx + (wid - 3)) : "memory");
        if (wid == 0) {
          float cs[8];
#pragma unroll
          for (int i = 0; i < 8; i++) cs[i] = 0.f;
          const uint4* wp = (const uint4*)(P.wq + (32 * (bid & 15) + (lane >> 3)) * D_ + 64 * (bid >> 4)) + (lane & 7);
#pragma unroll
          for (int h = 0; h < 8; h++) {
            const uint4 v = __ldg(wp + h * 256);
            cs[0] += bf_lo(v.x); cs[1] += bf_hi(v.x); cs[2] += bf_lo(v.y); cs[3] += bf_hi(v.y);
            cs[4] += bf_lo(v.z); cs[5] += bf_hi(v.z); cs[6] += bf_lo(v.w); cs[7] += bf_hi(v.w);
          }
#pragma unroll
          for (int i = 0; i < 8; i++) { cs[i] += __shfl_xor_sync(~0u, cs[i], 8); cs[i] += __shfl_xor_sync(~0u, cs[i], 16); }
          if (lane < 8) {
            *(float4*)(g_kv + (R_CS + 2 * lane) * 2048 + bid * 16) = make_float4(cs[0], cs[1], cs[2], cs[3]);
            *(float4*)(g_kv + (R_CS + 2 * lane + 1) * 2048 + bid * 16) = make_float4(cs[4], cs[5], cs[6], cs[7]);
          }
        }
        if (wid == 2 && elect_one()) {
          const uint32_t done = *(volatile unsigned int*)&g_cnt[C_DONE * CNT_STRIDE];
#pragma unroll
          for (int i = B_KV0; i < B_NUM; i++)
            mbar_init(bars + 8 * i, i < B_WO ? 1 : i < B_RE ? 2 : i < B_W1E ? 4 : i < B_ADONE ? 8 : 16);
#pragma unroll
          for (int i = 1; i < 7; i++) sc[i] = 0;
          sc[SC_EPOCH] = done / NCTA;
          asm volatile("fence.mbarrier_init.release.cluster;" ::: "memory");
        }
        __syncwarp();
        if (wid == 0 || wid == 2) asm volatile("bar.arrive 7, 320;" ::: "memory");
      }
      undef(qacc);
      const bool lead = elect_one();
      bar_sync(6, 512);
#pragma unroll 1
      for (int k = 0; k < 8; k++) {
        mbar_wait(bars + 8 * (B_XQ + k), 0);
        const uint64_t da = mkdesc(sb + OFF_X + wg * 8 * KB, 16, 1024, 1) + 1024 * k, db = mkdesc(sb + OFF_WQ, 8192, 1024, 1) + 512 * k;
        wg_fence();
#pragma unroll
        for (int s = 0; s < 4; s++) wgmma_n64_bt(qacc, da + 2 * s, db + 128 * s, s ? 1 : k);
        wg_commit();
        wg_wait<1>();
        if (k == 4 && lead) mbar_arrive(bars + 8 * B_X01);
      }
      wg_wait<0>();
      pin(qacc);
      if (lead) mbar_arrive(bars + 8 * B_XALL);
      if (tid == 0) TSTAMP(1);
      mbar_wait(bars + 8 * B_QS, 0);
      mbar_wait(bars + 8 * B_XALL, 0);
      const float2* sp = (const float2*)(smem + OFF_ST1) + wid * 16 + (lane >> 2);
      const float2 st0 = sp[0], st1 = sp[8];
      const float2* cs = (const float2*)(smem + OFF_CSQ) + (lane & 3);
      const float r0 = st0.y * QK_SCALE_LOG2, r1 = st1.y * QK_SCALE_LOG2, m0 = -st0.x * r0, m1 = -st1.x * r1;
      uint32_t nmax = 0;
#pragma unroll
      for (int h = 0; h < 4; h++) {
        uint32_t qh[4];
#pragma unroll
        for (int b = 2 * h; b < 2 * h + 2; b++) {
          const float2 cc = cs[4 * b];
          qacc[4 * b] = fmaf(qacc[4 * b], r0, m0 * cc.x); qacc[4 * b + 1] = fmaf(qacc[4 * b + 1], r0, m0 * cc.y);
          qacc[4 * b + 2] = fmaf(qacc[4 * b + 2], r1, m1 * cc.x); qacc[4 * b + 3] = fmaf(qacc[4 * b + 3], r1, m1 * cc.y);
          qh[2 * (b & 1)] = pack_f16(qacc[4 * b], qacc[4 * b + 1]);
          qh[2 * (b & 1) + 1] = pack_f16(qacc[4 * b + 2], qacc[4 * b + 3]);
        }
        stsm4(qdst + h * 2048, qh[0], qh[1], qh[2], qh[3]);
        float u[4], v[4];
        mma16816h(u, qh[0], qh[1], qh[2], qh[3], qh[0], qh[2]);
        mma16816h(v, qh[0], qh[1], qh[2], qh[3], qh[1], qh[3]);
        nmax = max(max(nmax, __float_as_uint(fabsf(u[0]))), __float_as_uint(fabsf(u[1])));
        nmax = max(max(nmax, __float_as_uint(fabsf(v[2]))), __float_as_uint(fabsf(v[3])));
      }
      nmax = __reduce_max_sync(~0u, nmax);
      if (lane == 0) atomicMax(&sc[SC_QMAX], nmax);
    } else {
      uint4 xr[4];
      const __nv_bfloat16* xp = P.x + (size_t)(bid * 16 + (lane >> 2)) * D_ + 64 * (wid - 8) + 8 * (lane & 3);
      xr[0] = __ldg((const uint4*)xp); xr[1] = __ldg((const uint4*)(xp + 8 * D_));
      xr[2] = __ldg((const uint4*)(xp + 32)); xr[3] = __ldg((const uint4*)(xp + 8 * D_ + 32));
      kv_path(smem, sb, xr);
      asm volatile("bar.arrive 6, 512;" ::: "memory");
      if (wid == 8) {
        if (elect_one()) {
          TSTAMP(27);
          flag_add(C_KV);
          TSTAMP(2);
        }
      } else if (wid < 12) {
        mbar_wait(bars + 8 * B_XALL, 0);
#pragma unroll 5
        for (int e = tid - 288; e < 1408; e += 96) *(uint4*)(smem + OFF_FILL + e * 16) = make_uint4(~0u, ~0u, ~0u, ~0u);
      } else {
        if (wid == 15) flag_wait(C_KV, (sc[SC_EPOCH] + 1) * NMAIN);
        bar_sync(5, 128);
        if (wid == 15) {
          if (elect_one()) {
            TSTAMP(3);
            mbar_wait(bars + 8 * B_X01, 0);
            mbar_expect(bars + 8 * B_KV0, 3 * CHB);
#pragma unroll 1
            for (int c = 0; c < 3; c++) bulk_g2s(sb + c * CHB, g_kv + c * CHB, CHB, bars + 8 * B_KV0);
            mbar_wait(bars + 8 * B_XALL, 0);
            mbar_wait(bars + 8 * B_QS, 0);
            mbar_expect(bars + 8 * B_KV1, 5 * CHB);
#pragma unroll 1
            for (int c = 3; c < 8; c++) bulk_g2s(sb + c * CHB, g_kv + c * CHB, CHB, bars + 8 * B_KV1);
          }
        } else if (wid == 14) {
          uint32_t km = 0, vm = 0;
#pragma unroll
          for (int i = 0; i < 4; i++) {
            const float4 a = __ldcg((const float4*)(g_kv + R_MX * 2048) + lane + 32 * i), b = __ldcg((const float4*)(g_kv + R_MX * 2048) + 128 + lane + 32 * i);
            km = max(km, __float_as_uint(a.x + a.y + a.z + a.w)); vm = max(vm, __float_as_uint(b.x + b.y + b.z + b.w));
          }
          km = __reduce_max_sync(~0u, km); vm = __reduce_max_sync(~0u, vm);
          if (lane == 0) { sc[SC_KMAX] = km; sc[SC_VMAX] = vm; }
        } else {
          if (wid == 13) {
            const float4* cp = (const float4*)(g_kv + (R_CS + (lane >> 1)) * 2048) + j * 16 + (lane & 1);
            float4 acc = __ldcg(cp);
#pragma unroll
            for (int i = 1; i < 8; i++) { const float4 v = __ldcg(cp + 2 * i); acc.x += v.x; acc.y += v.y; acc.z += v.z; acc.w += v.w; }
            acc.x += __shfl_xor_sync(~0u, acc.x, 1); acc.y += __shfl_xor_sync(~0u, acc.y, 1);
            acc.z += __shfl_xor_sync(~0u, acc.z, 1); acc.w += __shfl_xor_sync(~0u, acc.w, 1);
            if (lane & 1) *(float4*)(smem + OFF_CSQ + (lane >> 1) * 16) = acc;
          } else {
            const float4* sp = (const float4*)(g_kv + (R_ST + (lane >> 3)) * 2048) + g * 8 + (lane & 7);
            const float4 u = __ldcg(sp), v = __ldcg(sp + 512);
            *(float4*)(smem + OFF_ST1 + (lane & 7) * 128 + (lane >> 3) * 16) = u;
            *(float4*)(smem + OFF_ST1 + (lane & 7) * 128 + (lane >> 3) * 16 + 64) = v;
          }
          __syncwarp();
          if (lane == 0) mbar_arrive(bars + 8 * B_QS);
          if (tid == 416) TSTAMP(26);
        }
      }
      __syncwarp();
    }
    fence_async_smem();
    __syncthreads();
    const float q2 = __uint_as_float(sc[SC_QMAX]), k2 = __uint_as_float(sc[SC_KMAX]), v2 = __uint_as_float(sc[SC_VMAX]);
    fast = __all_sync(~0u, (q2 * k2 <= 56.f * 56.f) && (q2 <= 1048576.f) && (k2 <= 1048576.f) && (v2 <= 1e24f));
    if (tid == 0) TSTAMP(4);
    if (!fast) {
      mbar_wait(bars + 8 * B_KV0, 0);
      mbar_wait(bars + 8 * B_KV1, 0);
      if (wg < 2) {
#pragma unroll
        for (int h = 0; h < 4; h++) {
          constexpr float u = 1.0f / QK_SCALE_LOG2;
          stsm4(qdst + h * 2048, pack_bf16(qacc[8 * h] * u, qacc[8 * h + 1] * u), pack_bf16(qacc[8 * h + 2] * u, qacc[8 * h + 3] * u),
                pack_bf16(qacc[8 * h + 4] * u, qacc[8 * h + 5] * u), pack_bf16(qacc[8 * h + 6] * u, qacc[8 * h + 7] * u));
        }
      }
      for (int e = tid; e < 4096; e += 512) *(uint4*)(smem + (e >> 9) * CHB + (e & 511) * 16) = __ldcg((const uint4*)(g_kv + R_KP * 2048) + e);
      fence_async_smem();
      __syncthreads();
    }
  }
  {
    const int wq = __shfl_sync(~0u, fresh_tid() >> 5, 0), wg = wq >> 2;
    if (fast) attention_fast(P, sb, wg, (wq == 5) + 2 * (wq == 13), (wq & 3) == 3);
    else attention_safe(P, sb, wg, (wq == 5) + 2 * (wq == 13), (wq & 3) == 3);
  }
  const int wid = __shfl_sync(~0u, fresh_tid() >> 5, 0);
  if (fresh_tid() == 0) TSTAMP(5);
  if ((wid & 4) == 0) {
    post_chain(P, smem, sb, wid < 4);
    if (fresh_tid() == 0) { asm volatile("red.relaxed.gpu.global.add.u32 [%0], 1;" ::"l"(&g_cnt[C_DONE * CNT_STRIDE]) : "memory"); TSTAMP(6); }
  } else {
    if (wid == 15) weight_producer(P, sb);
    else if (wid == 7) ln2_stats(smem, sb);
    else ring_producer(sb, wid >= 8 ? wid & 3 : wid - 1);
  }
}

__device__ __forceinline__ float bfr(float v) { return bf_lo(pack_bf16(v, 0.f)); }
__device__ __forceinline__ float ldbf(const __nv_bfloat16* p) { return __bfloat162float(*p); }
__device__ void ln_row(float* v, float* red) {
  const int t = threadIdx.x;
  if (t < 32) {
    float s = 0.f, q = 0.f;
    for (int i = t; i < D_; i += 32) s += v[i];
    for (int o = 16; o; o >>= 1) s += __shfl_xor_sync(~0u, s, o);
    s *= 1.0f / D_;
    for (int i = t; i < D_; i += 32) q += (v[i] - s) * (v[i] - s);
    for (int o = 16; o; o >>= 1) q += __shfl_xor_sync(~0u, q, o);
    if (t == 0) { red[0] = s; red[1] = rsqrtf(q * (1.0f / D_) + LN_EPS); }
  }
  __syncthreads();
  if (t < D_) v[t] = bfr((v[t] - red[0]) * red[1]);
  __syncthreads();
}
__global__ void __launch_bounds__(1024) plain_qkv(const __grid_constant__ Params P) {
  __shared__ float v[D_], red[2];
  const int t = threadIdx.x;
  if (t < D_) v[t] = ldbf(P.x + blockIdx.x * D_ + t);
  __syncthreads();
  ln_row(v, red);
  if (t < 544) {
    const __nv_bfloat16* w = t < 512 ? P.wq + t : t < 528 ? P.wk + t - 512 : P.wv + t - 528;
    const int ld = t < 512 ? D_ : 16;
    float a = 0.f;
    for (int k = 0; k < D_; k++) a = fmaf(v[k], ldbf(w + k * ld), a);
    ((float*)g_act)[blockIdx.x * 544 + t] = bfr(a);
  }
}
__global__ void __launch_bounds__(1024) plain_rest(const __grid_constant__ Params P) {
  __shared__ float v[D_], h[D_], f[F_], red[2];
  const int t = threadIdx.x, lane = t & 31;
  const float* qkv = (const float*)g_act;
  float q[16], o[16], m = -INFINITY, l = 0.f;
#pragma unroll
  for (int d = 0; d < 16; d++) { q[d] = qkv[blockIdx.x * 544 + (t >> 5) * 16 + d]; o[d] = 0.f; }
  for (int k = lane; k < S_; k += 32) {
    float s = 0.f;
#pragma unroll
    for (int d = 0; d < 16; d++) s = fmaf(q[d], qkv[k * 544 + 512 + d], s);
    const float mn = fmaxf(m, s), r = exp2f((m - mn) * QK_SCALE_LOG2), p = exp2f((s - mn) * QK_SCALE_LOG2);
    l = l * r + p; m = mn;
#pragma unroll
    for (int d = 0; d < 16; d++) o[d] = o[d] * r + p * qkv[k * 544 + 528 + d];
  }
  float mx = m;
  for (int s = 16; s; s >>= 1) mx = fmaxf(mx, __shfl_xor_sync(~0u, mx, s));
  const float r = exp2f((m - mx) * QK_SCALE_LOG2);
  l *= r;
  for (int s = 16; s; s >>= 1) l += __shfl_xor_sync(~0u, l, s);
#pragma unroll
  for (int d = 0; d < 16; d++) {
    float a = o[d] * r;
    for (int s = 16; s; s >>= 1) a += __shfl_xor_sync(~0u, a, s);
    if (lane == 0) f[(t >> 5) * 16 + d] = bfr(a / l);
  }
  __syncthreads();
  if (t < D_) {
    float a = ldbf(P.x + blockIdx.x * D_ + t);
    for (int k = 0; k < D_; k++) a = fmaf(f[k], ldbf(P.wo + k * D_ + t), a);
    v[t] = h[t] = bfr(a);
  }
  __syncthreads();
  ln_row(v, red);
  for (int c = t; c < F_; c += 1024) {
    float a = 0.f;
    for (int k = 0; k < D_; k++) a = fmaf(v[k], ldbf(P.w1 + k * F_ + c), a);
    f[c] = bfr(a / (1.0f + expf(-a)));
  }
  __syncthreads();
  if (t < D_) {
    float a = h[t];
    for (int k = 0; k < F_; k++) a = fmaf(f[k], ldbf(P.w2 + k * D_ + t), a);
    P.out[blockIdx.x * D_ + t] = __float2bfloat16(a);
  }
}

typedef CUresult (*EncodeFn)(CUtensorMap*, CUtensorMapDataType, cuuint32_t, void*, const cuuint64_t*, const cuuint64_t*, const cuuint32_t*,
                             const cuuint32_t*, CUtensorMapInterleave, CUtensorMapSwizzle, CUtensorMapL2promotion, CUtensorMapFloatOOBfill);

void make_map(EncodeFn enc, CUtensorMap* m, const void* ptr, int rows, int cols, int box_rows) {
  cuuint64_t dims[2] = {(cuuint64_t)cols, (cuuint64_t)rows}, strides[1] = {(cuuint64_t)cols * 2};
  cuuint32_t box[2] = {64, (cuuint32_t)box_rows}, es[2] = {1, 1};
  enc(m, CU_TENSOR_MAP_DATA_TYPE_BFLOAT16, 2, (void*)ptr, dims, strides, box, es, CU_TENSOR_MAP_INTERLEAVE_NONE,
      CU_TENSOR_MAP_SWIZZLE_128B, CU_TENSOR_MAP_L2_PROMOTION_L2_128B, CU_TENSOR_MAP_FLOAT_OOB_FILL_NONE);
}

}

extern "C" void kernel_launch(void* const* d_in, const int* in_sizes, int n_in, void* d_out, int out_size) {
  (void)in_sizes; (void)n_in; (void)out_size;
  static EncodeFn enc = nullptr;
  static int clusters = 0;
  if (!enc) {
    cudaDriverEntryPointQueryResult qr;
    void* fn = nullptr;
    cudaGetDriverEntryPoint("cuTensorMapEncodeTiled", &fn, cudaEnableDefault, &qr);
    enc = (EncodeFn)fn;
    cudaFuncSetAttribute(fused_block_kernel, cudaFuncAttributeMaxDynamicSharedMemorySize, SMEM_BYTES);
    cudaLaunchConfig_t cfg = {};
    cfg.gridDim = dim3(NCTA); cfg.blockDim = dim3(512); cfg.dynamicSmemBytes = SMEM_BYTES;
    if (cudaOccupancyMaxActiveClusters(&clusters, fused_block_kernel, &cfg) != cudaSuccess) { clusters = 0; (void)cudaGetLastError(); }
  }
  Params P;
  const __nv_bfloat16* x = (const __nv_bfloat16*)d_in[0];
  make_map(enc, &P.tx, x, S_, D_, 128);
  make_map(enc, &P.twq, d_in[1], D_, D_, 64);
  make_map(enc, &P.two, d_in[4], D_, D_, 256);
  make_map(enc, &P.tw2, d_in[7], F_, D_, 64);
  P.x = x; P.wq = (const __nv_bfloat16*)d_in[1]; P.wk = (const __nv_bfloat16*)d_in[2]; P.wv = (const __nv_bfloat16*)d_in[3];
  P.wo = (const __nv_bfloat16*)d_in[4]; P.w1 = (const __nv_bfloat16*)d_in[6]; P.w2 = (const __nv_bfloat16*)d_in[7];
  P.out = (__nv_bfloat16*)d_out;
  P.c1 = 0xBF00BF00u; P.c2 = 0x00030003u; P.c3 = 0x9F809F80u;
  if (clusters >= NCTA / 2) {
    fused_block_kernel<<<NCTA, 512, SMEM_BYTES>>>(P);
  } else {
    plain_qkv<<<S_, 1024>>>(P);
    plain_rest<<<S_, 1024>>>(P);
  }
}
```
